```python
import torch

def _softmax(x, axis=-1):
    return torch.softmax(x, dim=axis)
def _gelu(x):
    return torch.nn.functional.gelu(x, approximate="tanh")
def _silu(x):
    return torch.nn.functional.silu(x)
def _sigmoid(x):
    return torch.sigmoid(x)
def _layernorm(x, axis=-1, eps=1e-5):
    m = x.mean(dim=axis, keepdim=True)
    v = x.var(dim=axis, keepdim=True, unbiased=False)
    return (x - m) / torch.sqrt(v + eps)
def _scatter_add(tgt, idx, src, axis=0):
    return tgt.clone().index_add_(axis, idx, src)
def _segment_sum(src, seg, n):
    out = torch.zeros((n,) + src.shape[1:], dtype=src.dtype)
    return out.index_add_(0, seg, src)
def _pad(x, pw):
    flat = tuple(v for pair in reversed(pw) for v in pair)
    return torch.nn.functional.pad(x, flat)

kernel_name = 'recurrent_scan__gqa_block_cached__geglu_ffn__decode'

def setup_inputs():

    _w = (lambda a: (lambda t: t.to(torch.bfloat16) if t.is_floating_point() else t)(torch.as_tensor(a)))
    def _A_setup():
        B, Sq, D = 8, 1, 576
        Hq, Hkv, Sk, Dh = 32, 16, 8192, 128
        assert Hq % Hkv == 0, (Hq, Hkv)
        return {
            "x": _w((lambda *s: torch.randn(*s, dtype=torch.bfloat16) * 0.05)(B, Sq, D)),
            "k_cache": _w((lambda *s: torch.randn(*s, dtype=torch.bfloat16) * 0.8)(B, Hkv, Sk, Dh)),
            "v_cache": _w((lambda *s: torch.randn(*s, dtype=torch.bfloat16) * 0.2)(B, Hkv, Sk, Dh)),
            "wq": _w((lambda *s: torch.randn(*s, dtype=torch.bfloat16) * 0.8)(D, Hq * Dh) * (D ** -0.5)),
            "wo": _w((lambda *s: torch.randn(*s, dtype=torch.bfloat16) * 0.2)(Hq * Dh, D) * ((Hq * Dh) ** -0.5)),
        }
    _A_in = _A_setup()

    def _B_setup():
        B, S, D, F = 8, 1, 576, 4608
        return {
            "x": _w((lambda *s: torch.randn(*s, dtype=torch.bfloat16) * 0.05)(B, S, D)),
            "w_gate": _w((lambda *s: torch.randn(*s, dtype=torch.bfloat16) * 0.1)(D, F)),
            "w_up": _w((lambda *s: torch.randn(*s, dtype=torch.bfloat16) * 0.1)(D, F)),
            "w_down": _w((lambda *s: torch.randn(*s, dtype=torch.bfloat16) * 0.1)(F, D)),
        }
    _B_in = _B_setup()

    return {
        "A_x": _A_in["x"],
        "A_k_cache": _A_in["k_cache"],
        "A_v_cache": _A_in["v_cache"],
        "A_wq": _A_in["wq"],
        "A_wo": _A_in["wo"],
        "B_x": _B_in["x"],
        "B_w_gate": _B_in["w_gate"],
        "B_w_up": _B_in["w_up"],
        "B_w_down": _B_in["w_down"],
    }

def reference(A_x, A_k_cache, A_v_cache, A_wq, A_wo, B_x, B_w_gate, B_w_up, B_w_down):
    def _A_ref(x, k_cache, v_cache, wq, wo):
        B, Sq, D = x.shape
        Hq, Dh = 32, 128
        Hkv = k_cache.shape[1]
        rep = Hq // Hkv
        q = (lambda x, *d: x.permute(*d))((x @ wq).reshape(B, Sq, Hq, Dh), 0, 2, 1, 3)
        k = (lambda x, n, axis: torch.repeat_interleave(x, n, dim=axis))(k_cache, rep, axis=1)
        v = (lambda x, n, axis: torch.repeat_interleave(x, n, dim=axis))(v_cache, rep, axis=1)
        scores = torch.einsum("bhqd,bhkd->bhqk", q, k) * (Dh ** -0.5)
        p = _softmax(scores, axis=-1)
        o = torch.einsum("bhqk,bhkd->bhqd", p, v)
        return (lambda x, *d: x.permute(*d))(o, 0, 2, 1, 3).reshape(B, Sq, Hq * Dh) @ wo

    def _B_ref(x, w_gate, w_up, w_down):
        return (_gelu(x @ w_gate) * (x @ w_up)) @ w_down

    x = A_x
    xn = _layernorm(x, axis=-1)
    s = _A_ref(xn, A_k_cache, A_v_cache, A_wq, A_wo)
    g = _silu(_B_ref(xn, B_w_gate, B_w_up, B_w_down))
    return x + s * g
```

```cpp
#include <cuda_runtime.h>
#include <cuda_bf16.h>
#include <cuda.h>
#include <stdint.h>

namespace {

typedef unsigned long long u64;

constexpr int DM = 576;
constexpr int FF = 4608;
constexpr int HD = 4096;
constexpr int NCHUNK = 8192;

constexpr int GRID = 132;
constexpr int NTHR = 256;
#define P_RING 5
#define P_LAG 6
#define P_MDELAY 3
#define P_LIM 2
#define P_LIM_START 3
#define P_LIM_TAIL 3
constexpr int RING = P_RING;
constexpr int SLOT_BYTES = 32768;
constexpr int NBUF = 16;
constexpr int LISTN = 32;
constexpr int LAG = P_LAG;
constexpr int MDELAY = P_MDELAY;

constexpr int XN_STRIDE = 584;
constexpr int ACT_STRIDE = 776;
constexpr int QROW = 272;
constexpr int OACC_STRIDE = 288;

constexpr int SM_RING = 0;
constexpr int SM_QBUF = SM_RING + RING * SLOT_BYTES;
constexpr int SM_SBUF = SM_QBUF + NBUF * 2 * QROW;
constexpr int SM_PBUF = SM_SBUF + NBUF * 512;
constexpr int SM_XN = SM_PBUF + 2 * 2 * QROW;
constexpr int SM_ACT = SM_XN + 8 * XN_STRIDE * 2;
constexpr int SM_STAGE = SM_ACT + 8 * ACT_STRIDE * 2;
constexpr int SM_MBUF = SM_STAGE + 8 * 64 * 2;
constexpr int SM_BARS = SM_MBUF + NBUF * 8;
constexpr int SM_LIST = SM_BARS + (2 * RING + NBUF + 1) * 8;
constexpr int SM_DESC = SM_LIST + LISTN * 4;
constexpr int SM_WMAX = SM_DESC + 8 * 4;
constexpr int SM_MISC = SM_WMAX + 8 * 4;
constexpr int SM_END = SM_MISC + 16;
constexpr int SMEM_BYTES = SM_END + 1024;
static_assert(SMEM_BYTES <= 232448, "shared memory budget");
static_assert(RING <= 8, "desc size");

enum { T_WQ = 0, T_WG = 1, T_WU = 2, T_K = 3, T_V = 4, T_WO = 5, T_WD = 6, T_ATTEND = 7, T_END = 8 };

struct __align__(128) Scratch {
    unsigned epoch;
    unsigned pad0[31];
    unsigned ctr[2][32];
    unsigned adone[2][32];
    u64 qtag[8 * (HD / 2)];
    u64 htag[8 * (FF / 2)];
    u64 mslot[NCHUNK];
    float oacc[2][128][OACC_STRIDE];
    u64 part[36][14][128];
};
__device__ Scratch g_s;

#define TL(i) do {} while (0)

constexpr int SPIN_LIMIT = 1 << 24;

__device__ __forceinline__ uint32_t smem_u32(const void* p) { return (uint32_t)__cvta_generic_to_shared(p); }
__device__ __forceinline__ void mbar_init(uint32_t bar, int cnt) {
    asm volatile("mbarrier.init.shared::cta.b64 [%0], %1;" ::"r"(bar), "r"(cnt) : "memory");
}
__device__ __forceinline__ void mbar_expect_tx(uint32_t bar, uint32_t bytes) {
    asm volatile("mbarrier.arrive.expect_tx.shared::cta.b64 _, [%0], %1;" ::"r"(bar), "r"(bytes) : "memory");
}
__device__ __forceinline__ void mbar_arrive(uint32_t bar) {
    asm volatile("mbarrier.arrive.shared::cta.b64 _, [%0];" ::"r"(bar) : "memory");
}
__device__ __forceinline__ void mbar_wait(uint32_t bar, uint32_t parity) {
    uint32_t ok;
    int it = 0;
    do {
        asm volatile(
            "{\n.reg .pred p;\nmbarrier.try_wait.parity.shared::cta.b64 p, [%1], %2;\nselp.u32 %0, 1, 0, p;\n}"
            : "=r"(ok)
            : "r"(bar), "r"(parity)
            : "memory");
        if (++it > SPIN_LIMIT) __trap();
    } while (!ok);
}
__device__ __forceinline__ void tma2d(uint32_t dst, const CUtensorMap* m, int c0, int c1, uint32_t bar, u64 pol) {
    asm volatile(
        "cp.async.bulk.tensor.2d.shared::cluster.global.mbarrier::complete_tx::bytes.L2::cache_hint [%0], [%1, {%3, %4}], [%2], %5;"
        ::"r"(dst), "l"(m), "r"(bar), "r"(c0), "r"(c1), "l"(pol) : "memory");
}
__device__ __forceinline__ void tma3d(uint32_t dst, const CUtensorMap* m, int c0, int c1, int c2, uint32_t bar, u64 pol) {
    asm volatile(
        "cp.async.bulk.tensor.3d.shared::cluster.global.mbarrier::complete_tx::bytes.L2::cache_hint [%0], [%1, {%3, %4, %5}], [%2], %6;"
        ::"r"(dst), "l"(m), "r"(bar), "r"(c0), "r"(c1), "r"(c2), "l"(pol) : "memory");
}
__device__ __forceinline__ void ldsm4(uint32_t (&r)[4], uint32_t addr) {
    asm volatile("ldmatrix.sync.aligned.m8n8.x4.shared.b16 {%0,%1,%2,%3}, [%4];"
                 : "=r"(r[0]), "=r"(r[1]), "=r"(r[2]), "=r"(r[3]) : "r"(addr) : "memory");
}
__device__ __forceinline__ void ldsm4t(uint32_t (&r)[4], uint32_t addr) {
    asm volatile("ldmatrix.sync.aligned.m8n8.x4.trans.shared.b16 {%0,%1,%2,%3}, [%4];"
                 : "=r"(r[0]), "=r"(r[1]), "=r"(r[2]), "=r"(r[3]) : "r"(addr) : "memory");
}
__device__ __forceinline__ void mma16816(float (&c)[4], const uint32_t (&a)[4], uint32_t b0, uint32_t b1) {
    asm volatile(
        "mma.sync.aligned.m16n8k16.row.col.f32.bf16.bf16.f32 {%0,%1,%2,%3}, {%4,%5,%6,%7}, {%8,%9}, {%0,%1,%2,%3};"
        : "+f"(c[0]), "+f"(c[1]), "+f"(c[2]), "+f"(c[3])
        : "r"(a[0]), "r"(a[1]), "r"(a[2]), "r"(a[3]), "r"(b0), "r"(b1));
}
__device__ __forceinline__ void ld_relaxed_v2(u64& a, u64& b, const u64* p) {
    asm volatile("ld.relaxed.gpu.global.v2.b64 {%0,%1}, [%2];" : "=l"(a), "=l"(b) : "l"(p) : "memory");
}
__device__ __forceinline__ u64 ld_relaxed(const u64* p) {
    u64 a;
    asm volatile("ld.relaxed.gpu.global.b64 %0, [%1];" : "=l"(a) : "l"(p) : "memory");
    return a;
}
__device__ __forceinline__ void st_relaxed_v2(u64* p, u64 a, u64 b) {
    asm volatile("st.relaxed.gpu.global.v2.b64 [%0], {%1,%2};" ::"l"(p), "l"(a), "l"(b) : "memory");
}
__device__ __forceinline__ void st_relaxed(u64* p, u64 a) {
    asm volatile("st.relaxed.gpu.global.b64 [%0], %1;" ::"l"(p), "l"(a) : "memory");
}
__device__ __forceinline__ void red_v4(float* p, float a, float b, float c, float d) {
    asm volatile("red.relaxed.gpu.global.add.v4.f32 [%0], {%1,%2,%3,%4};" ::"l"(p), "f"(a), "f"(b), "f"(c), "f"(d) : "memory");
}
__device__ __forceinline__ uint32_t lds_v32(uint32_t addr) {
    uint32_t v;
    asm volatile("ld.volatile.shared.u32 %0, [%1];" : "=r"(v) : "r"(addr) : "memory");
    return v;
}
__device__ __forceinline__ void sts_v32(uint32_t addr, uint32_t v) {
    asm volatile("st.volatile.shared.u32 [%0], %1;" ::"r"(addr), "r"(v) : "memory");
}
__device__ __forceinline__ u64 lds_v64(uint32_t addr) {
    u64 v;
    asm volatile("ld.volatile.shared.u64 %0, [%1];" : "=l"(v) : "r"(addr) : "memory");
    return v;
}
__device__ __forceinline__ void sts_v64(uint32_t addr, u64 v) {
    asm volatile("st.volatile.shared.u64 [%0], %1;" ::"r"(addr), "l"(v) : "memory");
}
__device__ __forceinline__ void sts16(uint32_t addr, uint32_t v) {
    asm volatile("st.shared.u16 [%0], %1;" ::"r"(addr), "h"((unsigned short)v) : "memory");
}
__device__ __forceinline__ void cons_sync() { asm volatile("bar.sync 1, 128;" ::: "memory"); }

__device__ __forceinline__ uint32_t pack_bf16(float lo, float hi) {
    uint32_t r;
    asm("cvt.rn.bf16x2.f32 %0, %1, %2;" : "=r"(r) : "f"(hi), "f"(lo));
    return r;
}
__device__ __forceinline__ float bf_lo(uint32_t v) { return __uint_as_float(v << 16); }
__device__ __forceinline__ float bf_hi(uint32_t v) { return __uint_as_float(v & 0xffff0000u); }
__device__ __forceinline__ float bfr(float x) { return __bfloat162float(__float2bfloat16_rn(x)); }
__device__ __forceinline__ uint32_t bf_bits(float x) { return (uint32_t)__bfloat16_as_ushort(__float2bfloat16_rn(x)); }
__device__ __forceinline__ uint32_t hmax2(uint32_t a, uint32_t b) {
    uint32_t r;
    asm("max.bf16x2 %0, %1, %2;" : "=r"(r) : "r"(a), "r"(b));
    return r;
}

template <int KSTEPS>
__device__ __forceinline__ void wtile_mma(float (&acc)[2][4], uint32_t a_addr, uint32_t b_addr) {
#pragma unroll
    for (int kk = 0; kk < KSTEPS / 2; kk++) {
        uint32_t b[4], a0[4], a1[4];
        ldsm4(b, b_addr + kk * 64);
        ldsm4t(a0, a_addr + (2 * kk) * 2048);
        ldsm4t(a1, a_addr + (2 * kk + 1) * 2048);
        mma16816(acc[0], a0, b[0], b[1]);
        mma16816(acc[1], a1, b[2], b[3]);
    }
}

__global__ void __launch_bounds__(NTHR, 1)
fused_decode_kernel(const __grid_constant__ CUtensorMap mapK, const __grid_constant__ CUtensorMap mapV,
                    const __grid_constant__ CUtensorMap mapWq, const __grid_constant__ CUtensorMap mapWg,
                    const __grid_constant__ CUtensorMap mapWu, const __grid_constant__ CUtensorMap mapWo,
                    const __grid_constant__ CUtensorMap mapWd, const __nv_bfloat16* __restrict__ x,
                    __nv_bfloat16* __restrict__ out) {
    extern __shared__ __align__(16) unsigned char smem_raw[];
    const uint32_t sb = (smem_u32(smem_raw) + 1023u) & ~1023u;
    const int tid = threadIdx.x, warp = tid >> 5, lane = tid & 31;
    const int cta = blockIdx.x;
    const uint32_t bar_full = sb + SM_BARS, bar_empty = bar_full + RING * 8, bar_qfull = bar_empty + RING * 8,
                   bar_act = bar_qfull + NBUF * 8;

    const int n_wq = cta < 64 ? 3 : 0;
    const int gu_unit = cta >= 64 ? cta - 64 : (cta < 4 ? 68 + cta : -1);
    const int n_start = n_wq + (gu_unit >= 0 ? 6 : 0);
    const int tail_type = cta < 72 ? T_WO : (cta < 126 ? T_WD : T_END);
    const int tail_u = cta < 72 ? cta : cta - 72;
    const int tail_cg = tail_u % 9, tail_rg = tail_u / 9;

    u64 pol;
    asm volatile("createpolicy.fractional.L2::evict_first.b64 %0, 1.0;" : "=l"(pol));

    auto issue_start_tile = [&](int i, int slot) {
        const uint32_t bar = bar_full + slot * 8, dst = sb + SM_RING + slot * SLOT_BYTES;
        if (i < n_wq) {
            sts_v32(sb + SM_DESC + slot * 4, T_WQ | (i << 4));
            mbar_expect_tx(bar, 192 * 128);
            tma2d(dst, &mapWq, cta * 64, i * 192, bar, pol);
        } else {
            const int k = i - n_wq;
            sts_v32(sb + SM_DESC + slot * 4, ((k & 1) ? T_WU : T_WG) | ((k >> 1) << 4));
            mbar_expect_tx(bar, 192 * 128);
            tma2d(dst, (k & 1) ? &mapWu : &mapWg, gu_unit * 64, (k >> 1) * 192, bar, pol);
        }
    };

    if (tid == 0) {
        TL(0);
#pragma unroll 1
        for (int s = 0; s < RING; s++) { mbar_init(bar_full + s * 8, 1); mbar_init(bar_empty + s * 8, 4); }
#pragma unroll 1
        for (int s = 0; s < NBUF + 1; s++) mbar_init(bar_qfull + s * 8, 1);
        asm volatile("fence.mbarrier_init.release.cluster;" ::: "memory");
        asm volatile("fence.proxy.async.shared::cta;" ::: "memory");
#pragma unroll 1
        for (int i = 0; i < P_LIM_START; i++) issue_start_tile(i, i);
    }
    if (tid == 32) {
        unsigned e;
        asm volatile("ld.relaxed.gpu.global.u32 %0, [%1];" : "=r"(e) : "l"(&g_s.epoch) : "memory");
        sts_v32(sb + SM_MISC, e);
        sts_v32(sb + SM_MISC + 4, 0);
        sts_v32(sb + SM_MISC + 8, 0);
    }
    if (tid >= 64 && tid < 64 + LISTN) sts_v32(sb + SM_LIST + (tid - 64) * 4, 0);
    if (tid >= 96 && tid < 96 + NBUF) sts_v64(sb + SM_MBUF + (tid - 96) * 8, 0);
    __syncwarp();
    {
        const uint32_t* xr = reinterpret_cast<const uint32_t*>(x + warp * DM);
        uint32_t xv[9];
        float sum = 0.f;
#pragma unroll
        for (int i = 0; i < 9; i++) { xv[i] = __ldg(xr + lane + 32 * i); sum += bf_lo(xv[i]) + bf_hi(xv[i]); }
#pragma unroll
        for (int o = 16; o; o >>= 1) sum += __shfl_xor_sync(~0u, sum, o);
        const float mean = sum * (1.f / DM);
        float var = 0.f;
#pragma unroll
        for (int i = 0; i < 9; i++) {
            float a = bf_lo(xv[i]) - mean, b = bf_hi(xv[i]) - mean;
            var += a * a + b * b;
        }
#pragma unroll
        for (int o = 16; o; o >>= 1) var += __shfl_xor_sync(~0u, var, o);
        const float mb = bfr(mean);
        const float den = bfr(sqrtf(bfr(bfr(var * (1.f / DM)) + 1e-5f)));
#pragma unroll
        for (int i = 0; i < 9; i++) {
            uint32_t v = pack_bf16(bfr(bf_lo(xv[i]) - mb) / den, bfr(bf_hi(xv[i]) - mb) / den);
            sts_v32(sb + SM_XN + warp * (XN_STRIDE * 2) + (lane + 32 * i) * 4, v);
        }
    }
    __syncthreads();
    const unsigned epoch = lds_v32(sb + SM_MISC);
    const uint32_t tag = epoch + 1u;
    const int par = epoch & 1;

    if (warp >= 4) {
        const int w = warp - 4, ct = tid - 128;
        const int g = lane >> 2, t = lane & 3, r8 = lane & 7, mi = lane >> 3;
        const uint32_t offK = (uint32_t)((32 * w + r8 + (mi & 1) * 8) * 128);
        const uint32_t xorK = (uint32_t)(((mi >> 1) ^ r8) << 4);
        const uint32_t rowT = (uint32_t)((r8 + (mi >> 1) * 8) * 128);
        const uint32_t offV0 = (uint32_t)((w >> 1) * 16384) + rowT + (uint32_t)((((4 * w & 7) + (mi & 1)) ^ r8) << 4);
        const uint32_t offV1 = (uint32_t)((w >> 1) * 16384) + rowT + (uint32_t)((((4 * w & 7) + 2 + (mi & 1)) ^ r8) << 4);
        const uint32_t offW = rowT + (uint32_t)(((2 * w + (mi & 1)) ^ r8) << 4);
        const uint32_t offB2 = (uint32_t)((lane & 1) * QROW + mi * 16);
        float accA[2][4], accB[2][4];
        int slot = 0, kj = 0, vj = 0;
        uint32_t ph = 0;
        while (true) {
            mbar_wait(bar_full + slot * 8, ph);
            const uint32_t d = lds_v32(sb + SM_DESC + slot * 4);
            const int type = d & 15;
            const uint32_t tile = sb + SM_RING + slot * SLOT_BYTES;
            if (type == T_K) {
                const int e = kj & (NBUF - 1);
                mbar_wait(bar_qfull + e * 8, (kj / NBUF) & 1);
                if (kj == 0 && ct == 0) TL(2);
                uint32_t qf[4][4];
#pragma unroll
                for (int n = 0; n < 4; n++) ldsm4(qf[n], sb + SM_QBUF + e * (2 * QROW) + offB2 + n * 64);
                float c0[4] = {0.f, 0.f, 0.f, 0.f}, c1[4] = {0.f, 0.f, 0.f, 0.f};
#pragma unroll
                for (int ks = 0; ks < 8; ks++) {
                    uint32_t a0[4], a1[4];
                    const uint32_t ad = tile + offK + (ks >> 2) * 16384 + (xorK ^ (uint32_t)((ks & 3) << 5));
                    ldsm4(a0, ad);
                    ldsm4(a1, ad + 2048);
                    mma16816(c0, a0, qf[ks >> 1][(ks & 1) * 2], qf[ks >> 1][(ks & 1) * 2 + 1]);
                    mma16816(c1, a1, qf[ks >> 1][(ks & 1) * 2], qf[ks >> 1][(ks & 1) * 2 + 1]);
                }
                __syncwarp();
                if (lane == 0) mbar_arrive(bar_empty + slot * 8);
                const float SC = 0.08838834764831845f;
                uint32_t s[4];
                s[0] = pack_bf16(c0[0], c0[1]); s[1] = pack_bf16(c0[2], c0[3]);
                s[2] = pack_bf16(c1[0], c1[1]); s[3] = pack_bf16(c1[2], c1[3]);
#pragma unroll
                for (int i = 0; i < 4; i++) s[i] = pack_bf16(bf_lo(s[i]) * SC, bf_hi(s[i]) * SC);
                const uint32_t mine = t == 0 ? s[0] : t == 1 ? s[1] : t == 2 ? s[2] : s[3];
                sts_v32(sb + SM_SBUF + e * 512 + (32 * w + 8 * t + g) * 4, mine);
                uint32_t m2 = hmax2(hmax2(s[0], s[1]), hmax2(s[2], s[3]));
                m2 = hmax2(m2, __shfl_xor_sync(~0u, m2, 4));
                m2 = hmax2(m2, __shfl_xor_sync(~0u, m2, 8));
                m2 = hmax2(m2, __shfl_xor_sync(~0u, m2, 16));
                const uint32_t wm = sb + SM_WMAX + (kj & 1) * 16;
                if (lane == 0) sts_v32(wm + w * 4, m2);
                cons_sync();
                if (ct == 0) {
                    m2 = hmax2(hmax2(m2, lds_v32(wm + 4)), hmax2(lds_v32(wm + 8), lds_v32(wm + 12)));
                    st_relaxed(&g_s.mslot[d >> 8], ((u64)tag << 32) | m2);
                }
                kj++;
            } else if (type == T_V) {
                const int e = vj & (NBUF - 1);
                const uint32_t M2 = (uint32_t)lds_v64(sb + SM_MBUF + e * 8);
                const uint32_t s2 = lds_v32(sb + SM_SBUF + e * 512 + ct * 4);
                const float L2E = 1.4426950408889634f;
                const float p0 = exp2f((bf_lo(s2) - bf_lo(M2)) * L2E), p1 = exp2f((bf_hi(s2) - bf_hi(M2)) * L2E);
                const uint32_t pp = pack_bf16(p0, p1);
                const uint32_t pb = sb + SM_PBUF + (vj & 1) * (2 * QROW);
                sts16(pb + ct * 2, pp & 0xffffu);
                sts16(pb + QROW + ct * 2, pp >> 16);
                cons_sync();
                if (ct == 0) sts_v32(sb + SM_MISC + 4, vj + 1);
                uint32_t pf[4][4];
#pragma unroll
                for (int n = 0; n < 4; n++) ldsm4(pf[n], pb + offB2 + n * 64);
                float c0[4] = {0.f, 0.f, 0.f, 0.f}, c1[4] = {0.f, 0.f, 0.f, 0.f}, cl[4] = {0.f, 0.f, 0.f, 0.f};
                const uint32_t ones[4] = {0x3f803f80u, 0x3f803f80u, 0x3f803f80u, 0x3f803f80u};
#pragma unroll
                for (int ks = 0; ks < 8; ks++) {
                    uint32_t a0[4], a1[4];
                    ldsm4t(a0, tile + offV0 + ks * 2048);
                    ldsm4t(a1, tile + offV1 + ks * 2048);
                    mma16816(c0, a0, pf[ks >> 1][(ks & 1) * 2], pf[ks >> 1][(ks & 1) * 2 + 1]);
                    mma16816(c1, a1, pf[ks >> 1][(ks & 1) * 2], pf[ks >> 1][(ks & 1) * 2 + 1]);
                    if ((ks >> 1) == w) mma16816(cl, ones, pf[ks >> 1][(ks & 1) * 2], pf[ks >> 1][(ks & 1) * 2 + 1]);
                }
                __syncwarp();
                if (lane == 0) mbar_arrive(bar_empty + slot * 8);
                float* oa = g_s.oacc[par][d >> 14];
                if (t < 2 || lane == 2) {
                    float v0, v1, v2, v3;
                    int idx;
                    if (t == 0) { v0 = c0[0]; v1 = c0[1]; v2 = c0[2]; v3 = c0[3]; idx = (2 * w * 8 + g) * 4; }
                    else if (t == 1) { v0 = c1[0]; v1 = c1[1]; v2 = c1[2]; v3 = c1[3]; idx = ((2 * w + 1) * 8 + g) * 4; }
                    else { v0 = cl[0]; v1 = cl[1]; v2 = 0.f; v3 = 0.f; idx = 256; }
                    red_v4(oa + idx, v0, v1, v2, v3);
                }
                vj++;
            } else if (type <= T_WU) {
                const int idx = (d >> 4) & 15;
                const uint32_t bad = sb + SM_XN + r8 * (XN_STRIDE * 2) + (idx * 192 + mi * 8) * 2;
                if (type == T_WU) {
                    if (idx == 0) {
#pragma unroll
                        for (int i = 0; i < 4; i++) accB[0][i] = accB[1][i] = 0.f;
                    }
                    wtile_mma<12>(accB, tile + offW, bad);
                } else {
                    if (idx == 0) {
#pragma unroll
                        for (int i = 0; i < 4; i++) accA[0][i] = accA[1][i] = 0.f;
                    }
                    wtile_mma<12>(accA, tile + offW, bad);
                }
                __syncwarp();
                if (lane == 0) mbar_arrive(bar_empty + slot * 8);
                if (idx == 2 && type != T_WG) {
#pragma unroll
                    for (int i = 0; i < 4; i++) {
                        float v = accA[0][i] + accA[1][i];
                        if (type == T_WU) {
                            const float gt = bfr(v), up = bfr(accB[0][i] + accB[1][i]);
                            const float inner = 0.7978845608028654f * (gt + 0.044715f * gt * gt * gt);
                            v = bfr(0.5f * gt * (1.f + tanhf(inner))) * up;
                        }
                        const int col = 16 * w + g + (i >> 1) * 8, b = 2 * t + (i & 1);
                        sts16(sb + SM_STAGE + (b * 64 + col) * 2, bf_bits(v));
                    }
                    cons_sync();
                    const int b = ct >> 4, c4 = ct & 15;
                    const u64 two = lds_v64(sb + SM_STAGE + (b * 64 + c4 * 4) * 2);
                    u64* dst = (type == T_WQ) ? &g_s.qtag[b * (HD / 2) + cta * 32 + c4 * 2]
                                              : &g_s.htag[b * (FF / 2) + gu_unit * 32 + c4 * 2];
                    st_relaxed_v2(dst, ((u64)tag << 32) | (two & 0xffffffffull), ((u64)tag << 32) | (two >> 32));
                    cons_sync();
                    if (ct == 0 && type == T_WQ) TL(1);
                }
            } else if (type == T_ATTEND) {
                if (lane == 0) mbar_arrive(bar_empty + slot * 8);
                cons_sync();
                if (ct == 0) {
                    TL(3);
                    __threadfence();
                    atomicAdd(&g_s.adone[par][0], 1u);
                    TL(4);
                }
                if (tail_type == T_WO) {
                    if (ct == 0) {
                        unsigned v;
                        int it = 0;
                        do {
                            asm volatile("ld.acquire.gpu.global.u32 %0, [%1];" : "=r"(v) : "l"(&g_s.adone[par][0]) : "memory");
                            if (++it > SPIN_LIMIT) __trap();
                        } while (v < GRID);
                        TL(5);
                        if (cta == 0) asm volatile("st.relaxed.gpu.global.u32 [%0], %1;" ::"l"(&g_s.epoch), "r"(epoch + 1u) : "memory");
                    }
                    cons_sync();
                    const int f = ct & 63, kvl = ct >> 6;
                    float4 ov[8];
                    float2 lv[8];
#pragma unroll
                    for (int b = 0; b < 8; b++) {
                        const float* oa = g_s.oacc[par][b * 16 + 2 * tail_rg + kvl];
                        ov[b] = __ldcg(reinterpret_cast<const float4*>(oa) + f);
                        lv[b] = __ldcg(reinterpret_cast<const float2*>(oa + 256));
                    }
                    const int dd = (f >> 3) * 16 + (f & 7);
#pragma unroll
                    for (int b = 0; b < 8; b++) {
                        const uint32_t ab = sb + SM_ACT + b * (ACT_STRIDE * 2) + (kvl * 256 + dd) * 2;
                        sts16(ab, bf_bits(ov[b].x / lv[b].x));
                        sts16(ab + 256, bf_bits(ov[b].y / lv[b].y));
                        sts16(ab + 16, bf_bits(ov[b].z / lv[b].x));
                        sts16(ab + 256 + 16, bf_bits(ov[b].w / lv[b].y));
                    }
                    cons_sync();
                    if (ct == 0) TL(6);
                } else if (tail_type == T_WD) {
                    mbar_wait(bar_act, 0);
                }
            } else if (type == T_WO || type == T_WD) {
                const int idx = (d >> 4) & 15;
                if (idx == 0) {
#pragma unroll
                    for (int i = 0; i < 4; i++) accA[0][i] = accA[1][i] = 0.f;
                }
                wtile_mma<16>(accA, tile + offW, sb + SM_ACT + r8 * (ACT_STRIDE * 2) + (idx * 256 + mi * 8) * 2);
                __syncwarp();
                if (lane == 0) mbar_arrive(bar_empty + slot * 8);
                if (idx == (type == T_WO ? 1 : 2)) {
                    u64* dst = &g_s.part[tail_cg * 4 + w][type == T_WO ? tail_rg : 8 + tail_rg][lane * 4];
                    const u64 th = (u64)tag << 32;
                    st_relaxed_v2(dst, th | __float_as_uint(accA[0][0] + accA[1][0]), th | __float_as_uint(accA[0][1] + accA[1][1]));
                    st_relaxed_v2(dst + 2, th | __float_as_uint(accA[0][2] + accA[1][2]), th | __float_as_uint(accA[0][3] + accA[1][3]));
                    if (ct == 0) TL(7);
                }
            } else {
                break;
            }
            if (++slot == RING) { slot = 0; ph ^= 1; }
        }
    } else {
        if (warp == 0) {
            if (lane == 0) {
                int n = P_LIM_START, landed = 0;
                int slot = P_LIM_START % RING, lslot = 0;
                uint32_t eph = (P_LIM_START >= RING) ? 0u : 1u, lph = 0;
                auto acquire = [&](int lim) {
                    while (n - landed >= lim) {
                        mbar_wait(bar_full + lslot * 8, lph);
                        landed++;
                        if (++lslot == RING) { lslot = 0; lph ^= 1; }
                    }
                    mbar_wait(bar_empty + slot * 8, eph);
                };
                auto advance = [&]() {
                    n++;
                    if (++slot == RING) { slot = 0; eph ^= 1; }
                };
                auto publish = [&](int j, uint32_t id) {
                    sts_v32(sb + SM_LIST + (j & (LISTN - 1)) * 4, (uint32_t)((j / LISTN + 1) << 16) | id);
                };
                unsigned* ctr = &g_s.ctr[par][0];
                int cur = cta;
                publish(0, cur);
                int nxt = (int)atomicAdd(ctr, 1u) + GRID;
                int grabbed = 2;
                bool have_nxt = true;
#pragma unroll 1
                for (int i = P_LIM_START; i < n_start; i++) {
                    acquire(P_LIM_START);
                    issue_start_tile(i, slot);
                    advance();
                }
                int kj = 0, vj = 0, spin = 0;
                bool exhausted = false;
                while (true) {
                    const bool v_elig = vj < kj && (kj - vj > LAG || exhausted);
                    if (v_elig && (uint32_t)(lds_v64(sb + SM_MBUF + (vj & (NBUF - 1)) * 8) >> 32) == (uint32_t)(vj + 1)) {
                        const uint32_t c = lds_v32(sb + SM_LIST + (vj & (LISTN - 1)) * 4) & 0xffffu;
                        acquire(P_LIM);
                        sts_v32(sb + SM_DESC + slot * 4, T_V | (c << 8));
                        mbar_expect_tx(bar_full + slot * 8, SLOT_BYTES);
                        tma3d(sb + SM_RING + slot * SLOT_BYTES, &mapV, 0, (int)c * 128, 0, bar_full + slot * 8, pol);
                        advance();
                        vj++;
                        spin = 0;
                        continue;
                    }
                    if (exhausted) {
                        if (vj == kj) break;
                        if (++spin > SPIN_LIMIT) __trap();
                        continue;
                    }
                    if (cur >= 0) {
                        acquire(P_LIM);
                        sts_v32(sb + SM_DESC + slot * 4, T_K | (cur << 8));
                        mbar_expect_tx(bar_full + slot * 8, SLOT_BYTES);
                        tma3d(sb + SM_RING + slot * SLOT_BYTES, &mapK, 0, cur * 128, 0, bar_full + slot * 8, pol);
                        advance();
                        kj++;
                        cur = -1;
                        spin = 0;
                    }
                    if (cur < 0 && have_nxt) {
                        have_nxt = false;
                        if (nxt >= NCHUNK) {
                            exhausted = true;
#pragma unroll 1
                            for (int i = 0; i < MDELAY + 2; i++) publish(kj + i, 0xffffu);
                            continue;
                        }
                        cur = nxt;
                        publish(kj, cur);
                    }
                    if (!have_nxt) {
                        if (grabbed - (int)lds_v32(sb + SM_MISC + 4) < NBUF) {
                            nxt = (int)atomicAdd(ctr, 1u) + GRID;
                            grabbed++;
                            have_nxt = true;
                        } else if (++spin > SPIN_LIMIT) __trap();
                    }
                }
                sts_v32(sb + SM_MISC + 8, 1);
                acquire(RING);
                sts_v32(sb + SM_DESC + slot * 4, T_ATTEND);
                mbar_arrive(bar_full + slot * 8);
                advance();
                const int n_tail = tail_type == T_WO ? 2 : (tail_type == T_WD ? 3 : 0);
#pragma unroll 1
                for (int i = 0; i < n_tail; i++) {
                    acquire(P_LIM_TAIL + 1);
                    sts_v32(sb + SM_DESC + slot * 4, tail_type | (i << 4));
                    mbar_expect_tx(bar_full + slot * 8, SLOT_BYTES);
                    if (tail_type == T_WO) tma2d(sb + SM_RING + slot * SLOT_BYTES, &mapWo, tail_cg * 64, tail_rg * 512 + i * 256, bar_full + slot * 8, pol);
                    else tma2d(sb + SM_RING + slot * SLOT_BYTES, &mapWd, tail_cg * 64, tail_rg * 768 + i * 256, bar_full + slot * 8, pol);
                    advance();
                }
                acquire(RING);
                sts_v32(sb + SM_DESC + slot * 4, T_END);
                mbar_arrive(bar_full + slot * 8);
            }
            __syncwarp();
        } else if (warp == 1) {
#pragma unroll 1
            for (int j = 0;; j++) {
                uint32_t ent;
                int it = 0;
                while (((ent = lds_v32(sb + SM_LIST + (j & (LISTN - 1)) * 4)) >> 16) != (uint32_t)(j / LISTN + 1)) {
                    __nanosleep(100);
                    if (++it > SPIN_LIMIT) __trap();
                }
                const uint32_t c = ent & 0xffffu;
                if (c == 0xffffu) break;
                const u64* src = &g_s.qtag[(c >> 6) * 128 + lane * 4];
                u64 a0, a1, a2, a3;
                it = 0;
                while (true) {
                    ld_relaxed_v2(a0, a1, src);
                    ld_relaxed_v2(a2, a3, src + 2);
                    const bool ok = (uint32_t)(a0 >> 32) == tag && (uint32_t)(a1 >> 32) == tag &&
                                    (uint32_t)(a2 >> 32) == tag && (uint32_t)(a3 >> 32) == tag;
                    if (__all_sync(~0u, ok)) break;
                    __nanosleep(200);
                    if (++it > SPIN_LIMIT) __trap();
                }
                const int e = j & (NBUF - 1);
                const uint32_t dst = sb + SM_QBUF + e * (2 * QROW) + (lane >> 4) * QROW + (lane & 15) * 16;
                asm volatile("st.shared.v4.u32 [%0], {%1,%2,%3,%4};" ::"r"(dst), "r"((uint32_t)a0), "r"((uint32_t)a1),
                             "r"((uint32_t)a2), "r"((uint32_t)a3) : "memory");
                __syncwarp();
                if (lane == 0) mbar_arrive(bar_qfull + e * 8);
            }
        } else if (warp == 2) {
#pragma unroll 1
            for (int j = 0;; j++) {
                int it = 0;
                const int jd = j + MDELAY + 1;
                while ((lds_v32(sb + SM_LIST + (jd & (LISTN - 1)) * 4) >> 16) != (uint32_t)(jd / LISTN + 1)) {
                    __nanosleep(100);
                    if (++it > SPIN_LIMIT) __trap();
                }
                const uint32_t c = lds_v32(sb + SM_LIST + (j & (LISTN - 1)) * 4) & 0xffffu;
                if (c == 0xffffu) break;
                const u64* src = &g_s.mslot[(c & ~63u) + lane * 2];
                u64 a0, a1;
                it = 0;
                while (true) {
                    ld_relaxed_v2(a0, a1, src);
                    const bool ok = (uint32_t)(a0 >> 32) == tag && (uint32_t)(a1 >> 32) == tag;
                    if (__all_sync(~0u, ok)) break;
                    __nanosleep(100);
                    if (++it > SPIN_LIMIT) __trap();
                }
                uint32_t m2 = hmax2((uint32_t)a0, (uint32_t)a1);
#pragma unroll
                for (int o = 16; o; o >>= 1) m2 = hmax2(m2, __shfl_xor_sync(~0u, m2, o));
                if (lane == 0) sts_v64(sb + SM_MBUF + (j & (NBUF - 1)) * 8, ((u64)(uint32_t)(j + 1) << 32) | m2);
            }
        } else {
            if (cta < 128) {
                float4* z = reinterpret_cast<float4*>(g_s.oacc[par ^ 1][cta]);
                for (int i = lane; i < OACC_STRIDE / 4; i += 32) z[i] = make_float4(0.f, 0.f, 0.f, 0.f);
            } else if (cta == 128 && lane == 0) {
                g_s.ctr[par ^ 1][0] = 0;
                g_s.adone[par ^ 1][0] = 0;
            }
            if (tail_type == T_WD) {
                __nanosleep(20000);
#pragma unroll 1
                for (int b = 0; b < 8; b++) {
                    const u64* src = &g_s.htag[b * (FF / 2) + tail_rg * 384 + lane * 2];
                    u64 a[12];
                    int it = 0;
                    while (true) {
                        bool ok = true;
#pragma unroll
                        for (int i = 0; i < 6; i++) ld_relaxed_v2(a[2 * i], a[2 * i + 1], src + i * 64);
#pragma unroll
                        for (int i = 0; i < 12; i++) ok = ok && (uint32_t)(a[i] >> 32) == tag;
                        if (__all_sync(~0u, ok)) break;
                        __nanosleep(500);
                        if (++it > SPIN_LIMIT) __trap();
                    }
#pragma unroll
                    for (int i = 0; i < 6; i++)
                        sts_v64(sb + SM_ACT + b * (ACT_STRIDE * 2) + (i * 64 + lane * 2) * 4,
                                (a[2 * i] & 0xffffffffull) | (a[2 * i + 1] << 32));
                }
                __syncwarp();
                if (lane == 0) mbar_arrive(bar_act);
            }
        }
        if (cta >= GRID - 36) {
            const int task = cta - (GRID - 36);
            const int pl = tid >> 2, i = tid & 3;
            const int col = (task >> 2) * 64 + (task & 3) * 16 + (pl >> 2) + (i >> 1) * 8, b = 2 * (pl & 3) + (i & 1);
            const float xv = __bfloat162float(x[b * DM + col]);
            const u64* src = &g_s.part[task][0][tid];
            u64 v[14];
            int it = 0;
            while (lds_v32(sb + SM_MISC + 8) == 0) {
                __nanosleep(200);
                if (++it > SPIN_LIMIT) __trap();
            }
            it = 0;
            while (true) {
                bool ok = true;
#pragma unroll
                for (int r = 0; r < 14; r++) v[r] = ld_relaxed(src + r * 128);
#pragma unroll
                for (int r = 0; r < 14; r++) ok = ok && (uint32_t)(v[r] >> 32) == tag;
                if (__all_sync(~0u, ok)) break;
                __nanosleep(50);
                if (++it > SPIN_LIMIT) __trap();
            }
            float s = 0.f, f = 0.f;
#pragma unroll
            for (int r = 0; r < 8; r++) s += __uint_as_float((uint32_t)v[r]);
#pragma unroll
            for (int r = 8; r < 14; r++) f += __uint_as_float((uint32_t)v[r]);
            s = bfr(s);
            f = bfr(f);
            const float gate = bfr(f / (1.f + expf(-f)));
            out[b * DM + col] = __float2bfloat16_rn(xv + bfr(s * gate));
            if (tid == 0) TL(8);
        }
    }
}

typedef CUresult (*EncodeFn)(CUtensorMap*, CUtensorMapDataType, cuuint32_t, void*, const cuuint64_t*, const cuuint64_t*,
                             const cuuint32_t*, const cuuint32_t*, CUtensorMapInterleave, CUtensorMapSwizzle,
                             CUtensorMapL2promotion, CUtensorMapFloatOOBfill);

void make_kv_map(EncodeFn enc, CUtensorMap* m, void* base) {
    cuuint64_t dims[3] = {64, (cuuint64_t)NCHUNK * 128, 2};
    cuuint64_t str[2] = {256, 128};
    cuuint32_t box[3] = {64, 128, 2};
    cuuint32_t es[3] = {1, 1, 1};
    enc(m, CU_TENSOR_MAP_DATA_TYPE_BFLOAT16, 3, base, dims, str, box, es, CU_TENSOR_MAP_INTERLEAVE_NONE,
        CU_TENSOR_MAP_SWIZZLE_128B, CU_TENSOR_MAP_L2_PROMOTION_L2_256B, CU_TENSOR_MAP_FLOAT_OOB_FILL_NONE);
}
void make_w_map(EncodeFn enc, CUtensorMap* m, void* base, int rows, int cols, int box_rows) {
    cuuint64_t dims[2] = {(cuuint64_t)cols, (cuuint64_t)rows};
    cuuint64_t str[1] = {(cuuint64_t)cols * 2};
    cuuint32_t box[2] = {64, (cuuint32_t)box_rows};
    cuuint32_t es[2] = {1, 1};
    enc(m, CU_TENSOR_MAP_DATA_TYPE_BFLOAT16, 2, base, dims, str, box, es, CU_TENSOR_MAP_INTERLEAVE_NONE,
        CU_TENSOR_MAP_SWIZZLE_128B, CU_TENSOR_MAP_L2_PROMOTION_L2_128B, CU_TENSOR_MAP_FLOAT_OOB_FILL_NONE);
}

}

extern "C" void kernel_launch(void* const* d_in, const int* in_sizes, int n_in, void* d_out, int out_size) {
    (void)in_sizes; (void)n_in; (void)out_size;
    static EncodeFn enc = nullptr;
    if (!enc) {
        void* fn = nullptr;
        cudaDriverEntryPointQueryResult qr;
        cudaGetDriverEntryPoint("cuTensorMapEncodeTiled", &fn, cudaEnableDefault, &qr);
        enc = (EncodeFn)fn;
        cudaFuncSetAttribute(fused_decode_kernel, cudaFuncAttributeMaxDynamicSharedMemorySize, SMEM_BYTES);
    }
    CUtensorMap mK, mV, mWq, mWg, mWu, mWo, mWd;
    make_kv_map(enc, &mK, d_in[1]);
    make_kv_map(enc, &mV, d_in[2]);
    make_w_map(enc, &mWq, d_in[3], DM, HD, 192);
    make_w_map(enc, &mWo, d_in[4], HD, DM, 256);
    make_w_map(enc, &mWg, d_in[6], DM, FF, 192);
    make_w_map(enc, &mWu, d_in[7], DM, FF, 192);
    make_w_map(enc, &mWd, d_in[8], FF, DM, 256);
    fused_decode_kernel<<<GRID, NTHR, SMEM_BYTES, cudaStreamPerThread>>>(
        mK, mV, mWq, mWg, mWu, mWo, mWd, (const __nv_bfloat16*)d_in[0], (__nv_bfloat16*)d_out);
}
```

```cpp
#include <cuda_runtime.h>
#include <cuda_bf16.h>
#include <cuda.h>
#include <stdint.h>

namespace {

typedef unsigned long long u64;

constexpr int DM = 576;
constexpr int FF = 4608;
constexpr int HD = 4096;
constexpr int NCHUNK = 8192;

constexpr int GRID = 132;
constexpr int NTHR = 256;
constexpr int RING = 5;
constexpr int SLOT_BYTES = 32768;
constexpr int NBUF = 16;
constexpr int LISTN = 32;
constexpr int LAG = 6;
constexpr int MDELAY = 4;
constexpr int LIM = 2;
constexpr int LIM_START = 3;
constexpr int NINIT = 3;
constexpr int NSTATK = 7;
constexpr int PRE_ROWS = 96;
constexpr double PACE = 1.0;
constexpr int PACE_CREDIT = 32;
constexpr uint32_t ISSUE_DELAY = 400;

constexpr int XN_STRIDE = 584;
constexpr int ACT_STRIDE = 776;
constexpr int QROW = 272;
constexpr int OACC_STRIDE = 384;

constexpr int SM_RING = 0;
constexpr int SM_QBUF = SM_RING + RING * SLOT_BYTES;
constexpr int SM_SBUF = SM_QBUF + NBUF * 2 * QROW;
constexpr int SM_XN = SM_SBUF + NBUF * 512;
constexpr int SM_ACT = SM_XN + 8 * XN_STRIDE * 2;
constexpr int SM_STAGE = SM_ACT + 8 * ACT_STRIDE * 2;
constexpr int SM_BARS = SM_STAGE + 8 * 64 * 2;
constexpr int NBARS = 2 * RING + 1 + 3 * NBUF;
constexpr int SM_LIST = SM_BARS + NBARS * 8;
constexpr int SM_DESC = SM_LIST + LISTN * 4;
constexpr int SM_WMAX = SM_DESC + 8 * 4;
constexpr int SM_MISC = SM_WMAX + 8 * 4;
constexpr int SM_LINV = (SM_MISC + 32 + 15) & ~15;
constexpr int SM_END = SM_LINV + 128;
constexpr int SMEM_BYTES = SM_END + 1024;
static_assert(SMEM_BYTES <= 232448, "shared memory budget");
static_assert(RING <= 8, "desc size");

enum { T_WQ = 0, T_WG = 1, T_WU = 2, T_K = 3, T_V = 4, T_WO = 5, T_WD = 6, T_END = 8 };

struct __align__(128) Scratch {
    unsigned epoch;
    unsigned pad0[31];
    unsigned ctr[2][32];
    u64 qtag[8 * (HD / 2)];
    u64 htag[8 * (FF / 2)];
    u64 mslot[NCHUNK];
    unsigned zflag[128];
    float oacc[128][OACC_STRIDE];
    float4 facc[36][4][32];
};
__device__ Scratch g_s;

__device__ __forceinline__ uint32_t smem_u32(const void* p) { return (uint32_t)__cvta_generic_to_shared(p); }
__device__ __forceinline__ void mbar_init(uint32_t bar, int cnt) {
    asm volatile("mbarrier.init.shared::cta.b64 [%0], %1;" ::"r"(bar), "r"(cnt) : "memory");
}
__device__ __forceinline__ void mbar_expect_tx(uint32_t bar, uint32_t bytes) {
    asm volatile("mbarrier.arrive.expect_tx.shared::cta.b64 _, [%0], %1;" ::"r"(bar), "r"(bytes) : "memory");
}
__device__ __forceinline__ void mbar_arrive(uint32_t bar) {
    asm volatile("mbarrier.arrive.shared::cta.b64 _, [%0];" ::"r"(bar) : "memory");
}
__device__ __forceinline__ uint32_t clk() {
    uint32_t c;
    asm volatile("mov.u32 %0, %clock;" : "=r"(c));
    return c;
}
__device__ __forceinline__ uint32_t now_ns() {
    uint32_t c;
    asm volatile("mov.u32 %0, %globaltimer_lo;" : "=r"(c));
    return c;
}
__device__ __forceinline__ void spin_guard(uint32_t t0) {
    if (clk() - t0 > 0x7fffffffu) __trap();
}
__device__ __forceinline__ bool mbar_try(uint32_t bar, uint32_t parity) {
    uint32_t ok;
    asm volatile("{\n.reg .pred p;\nmbarrier.try_wait.parity.shared::cta.b64 p, [%1], %2;\nselp.u32 %0, 1, 0, p;\n}"
                 : "=r"(ok) : "r"(bar), "r"(parity) : "memory");
    return ok;
}
__device__ __forceinline__ void mbar_wait(uint32_t bar, uint32_t parity) {
    const uint32_t t0 = clk();
    while (!mbar_try(bar, parity)) spin_guard(t0);
}
__device__ __forceinline__ bool mbar_test(uint32_t bar, uint32_t parity) {
    uint32_t ok;
    asm volatile("{\n.reg .pred p;\nmbarrier.test_wait.parity.shared::cta.b64 p, [%1], %2;\nselp.u32 %0, 1, 0, p;\n}"
                 : "=r"(ok) : "r"(bar), "r"(parity) : "memory");
    return ok;
}
__device__ __forceinline__ void mbar_spin(uint32_t bar, uint32_t parity) {
    const uint32_t t0 = clk();
    while (!mbar_test(bar, parity)) spin_guard(t0);
}
__device__ __forceinline__ void tma3d(uint32_t dst, const CUtensorMap* m, int c0, int c1, int c2, uint32_t bar, u64 pol) {
    asm volatile(
        "cp.async.bulk.tensor.3d.shared::cluster.global.mbarrier::complete_tx::bytes.L2::cache_hint [%0], [%1, {%3, %4, %5}], [%2], %6;"
        ::"r"(dst), "l"(m), "r"(bar), "r"(c0), "r"(c1), "r"(c2), "l"(pol) : "memory");
}
__device__ __forceinline__ void ldsm4(uint32_t (&r)[4], uint32_t addr) {
    asm volatile("ldmatrix.sync.aligned.m8n8.x4.shared.b16 {%0,%1,%2,%3}, [%4];"
                 : "=r"(r[0]), "=r"(r[1]), "=r"(r[2]), "=r"(r[3]) : "r"(addr) : "memory");
}
__device__ __forceinline__ void ldsm4t(uint32_t (&r)[4], uint32_t addr) {
    asm volatile("ldmatrix.sync.aligned.m8n8.x4.trans.shared.b16 {%0,%1,%2,%3}, [%4];"
                 : "=r"(r[0]), "=r"(r[1]), "=r"(r[2]), "=r"(r[3]) : "r"(addr) : "memory");
}
__device__ __forceinline__ void mma16816(float (&c)[4], const uint32_t (&a)[4], uint32_t b0, uint32_t b1) {
    asm volatile(
        "mma.sync.aligned.m16n8k16.row.col.f32.bf16.bf16.f32 {%0,%1,%2,%3}, {%4,%5,%6,%7}, {%8,%9}, {%0,%1,%2,%3};"
        : "+f"(c[0]), "+f"(c[1]), "+f"(c[2]), "+f"(c[3])
        : "r"(a[0]), "r"(a[1]), "r"(a[2]), "r"(a[3]), "r"(b0), "r"(b1));
}
__device__ __forceinline__ void ld_relaxed_v2(u64& a, u64& b, const u64* p) {
    asm volatile("ld.relaxed.gpu.global.v2.b64 {%0,%1}, [%2];" : "=l"(a), "=l"(b) : "l"(p) : "memory");
}
__device__ __forceinline__ void st_relaxed_v2(u64* p, u64 a, u64 b) {
    asm volatile("st.relaxed.gpu.global.v2.b64 [%0], {%1,%2};" ::"l"(p), "l"(a), "l"(b) : "memory");
}
__device__ __forceinline__ void atom_v4(float4& o, float4* p, float a, float b, float c) {
    asm volatile("atom.relaxed.gpu.global.add.v4.f32 {%0,%1,%2,%3}, [%4], {%5,%6,%7,0f00000000};"
                 : "=f"(o.x), "=f"(o.y), "=f"(o.z), "=f"(o.w) : "l"(p), "f"(a), "f"(b), "f"(c) : "memory");
}
__device__ __forceinline__ void ld_relaxed_f4(float4& v, const float4* p) {
    asm volatile("ld.relaxed.gpu.global.v4.f32 {%0,%1,%2,%3}, [%4];" : "=f"(v.x), "=f"(v.y), "=f"(v.z), "=f"(v.w) : "l"(p) : "memory");
}
__device__ __forceinline__ void st_relaxed(u64* p, u64 a) {
    asm volatile("st.relaxed.gpu.global.b64 [%0], %1;" ::"l"(p), "l"(a) : "memory");
}
__device__ __forceinline__ void red_v4(float* p, float a, float b, float c, float d) {
    asm volatile("red.relaxed.gpu.global.add.v4.f32 [%0], {%1,%2,%3,%4};" ::"l"(p), "f"(a), "f"(b), "f"(c), "f"(d) : "memory");
}
__device__ __forceinline__ uint32_t lds_v32(uint32_t addr) {
    uint32_t v;
    asm volatile("ld.volatile.shared.u32 %0, [%1];" : "=r"(v) : "r"(addr) : "memory");
    return v;
}
__device__ __forceinline__ void sts_v32(uint32_t addr, uint32_t v) {
    asm volatile("st.volatile.shared.u32 [%0], %1;" ::"r"(addr), "r"(v) : "memory");
}
__device__ __forceinline__ u64 lds_v64(uint32_t addr) {
    u64 v;
    asm volatile("ld.volatile.shared.u64 %0, [%1];" : "=l"(v) : "r"(addr) : "memory");
    return v;
}
__device__ __forceinline__ void sts_v64(uint32_t addr, u64 v) {
    asm volatile("st.volatile.shared.u64 [%0], %1;" ::"r"(addr), "l"(v) : "memory");
}
__device__ __forceinline__ void sts16(uint32_t addr, uint32_t v) {
    asm volatile("st.shared.u16 [%0], %1;" ::"r"(addr), "h"((unsigned short)v) : "memory");
}
__device__ __forceinline__ void cons_sync() { asm volatile("bar.sync 1, 128;" ::: "memory"); }

__device__ __forceinline__ uint32_t pack_bf16(float lo, float hi) {
    uint32_t r;
    asm("cvt.rn.bf16x2.f32 %0, %1, %2;" : "=r"(r) : "f"(hi), "f"(lo));
    return r;
}
__device__ __forceinline__ float bf_lo(uint32_t v) { return __uint_as_float(v << 16); }
__device__ __forceinline__ float bf_hi(uint32_t v) { return __uint_as_float(v & 0xffff0000u); }
__device__ __forceinline__ float bfr(float x) { return __bfloat162float(__float2bfloat16_rn(x)); }
__device__ __forceinline__ uint32_t bf_bits(float x) { return (uint32_t)__bfloat16_as_ushort(__float2bfloat16_rn(x)); }
__device__ __forceinline__ uint32_t hmax2(uint32_t a, uint32_t b) {
    uint32_t r;
    asm("max.bf16x2 %0, %1, %2;" : "=r"(r) : "r"(a), "r"(b));
    return r;
}

template <int KSTEPS>
__device__ __forceinline__ void wtile_mma(float (&acc)[2][4], uint32_t a_addr, uint32_t b_addr) {
    uint32_t b[KSTEPS / 2][4], a[KSTEPS][4];
#pragma unroll
    for (int kk = 0; kk < KSTEPS / 2; kk++) {
        ldsm4(b[kk], b_addr + kk * 64);
        ldsm4t(a[2 * kk], a_addr + (2 * kk) * 2048);
        ldsm4t(a[2 * kk + 1], a_addr + (2 * kk + 1) * 2048);
    }
#pragma unroll
    for (int kk = 0; kk < KSTEPS / 2; kk++) {
        mma16816(acc[0], a[2 * kk], b[kk][0], b[kk][1]);
        mma16816(acc[1], a[2 * kk + 1], b[kk][2], b[kk][3]);
    }
}

struct Maps { CUtensorMap m[7]; };

__global__ void __launch_bounds__(NTHR, 1)
fused_decode_kernel(const char* __restrict__ wq, const char* __restrict__ wg, const char* __restrict__ wu,
                    const __nv_bfloat16* __restrict__ x, __nv_bfloat16* __restrict__ out, const uint32_t pace_ns,
                    const __grid_constant__ Maps maps) {
    extern __shared__ __align__(16) unsigned char smem_raw[];
    const int tid = threadIdx.x, cta = blockIdx.x;
    if (tid == 32 && cta < 128) {
        constexpr uint32_t bq = PRE_ROWS * HD * 2 / 128, bf = PRE_ROWS * FF * 2 / 128;
        asm volatile("cp.async.bulk.prefetch.L2.global [%0], %1;" ::"l"(wq + (size_t)cta * bq), "n"(bq) : "memory");
        asm volatile("cp.async.bulk.prefetch.L2.global [%0], %1;" ::"l"(wg + (size_t)cta * bf), "n"(bf) : "memory");
        asm volatile("cp.async.bulk.prefetch.L2.global [%0], %1;" ::"l"(wu + (size_t)cta * bf), "n"(bf) : "memory");
    }
    const uint32_t sb = (smem_u32(smem_raw) + 1023u) & ~1023u;
    const uint32_t bar_full = sb + SM_BARS, bar_empty = bar_full + RING * 8, bar_act = bar_empty + RING * 8,
                   bar_qfull = bar_act + 8, bar_sfull = bar_qfull + NBUF * 8, bar_pfull = bar_sfull + NBUF * 8;
    u64 pol;
    asm volatile("createpolicy.fractional.L2::evict_first.b64 %0, 1.0;" : "=l"(pol));
    if (tid == 0) {
        static_assert(NINIT <= 3, "the first tiles are weight tiles");
#pragma unroll
        for (int i = 0; i < NINIT; i++) {
            const uint32_t desc = cta < 64 ? (T_WQ | (i << 4)) : (((i & 1) ? T_WU : T_WG) | ((i >> 1) << 4));
            mbar_init(bar_full + i * 8, 1);
            asm volatile("fence.mbarrier_init.release.cluster;" ::: "memory");
            sts_v32(sb + SM_DESC + i * 4, desc);
            mbar_expect_tx(bar_full + i * 8, 192 * 128);
            tma3d(sb + SM_RING + i * SLOT_BYTES, &maps.m[desc & 15], (cta & 63) * 64 + (cta >> 7) * 4096, (desc >> 4) * 192, 0,
                  bar_full + i * 8, pol);
        }
    }
    unsigned epoch_raw;
    asm volatile("ld.relaxed.gpu.global.u32 %0, [%1];" : "=r"(epoch_raw) : "l"(&g_s.epoch) : "memory");
    auto take_epoch = [&]() {
        unsigned e;
        asm volatile("mov.u32 %0, %1;" : "=r"(e) : "r"(epoch_raw) : "memory");
        return e;
    };
    const int warp = tid >> 5, lane = tid & 31;

    const int n_wq = cta < 64 ? 3 : 0;
    const int gu_unit = cta >= 64 ? cta - 64 : (cta < 4 ? 68 + cta : -1);
    const int n_start = n_wq + (gu_unit >= 0 ? 6 : 0);

    if (warp == 0) {
        const int n_stat = cta >= 4 ? NSTATK : 0;
        auto static_id = [&](int i) {
            return i < 6 ? (i - 3) * 60 + cta - 4
                         : (i < NSTATK + 3 ? 180 + (i - 6) * 128 + cta - 4 : 180 + (NSTATK - 3) * 128 + (i - NSTATK - 3) * 68 + cta - 64);
        };
        auto static_tile = [&](int i, uint32_t& desc, int& c0, int& c1, uint32_t& bytes) {
            const int k = i - n_wq;
            bytes = 192 * 128;
            if (k < 0) { desc = T_WQ | (i << 4); c0 = cta * 64; c1 = i * 192; }
            else if (i < n_start) { desc = ((k & 1) ? T_WU : T_WG) | ((k >> 1) << 4); c0 = gu_unit * 64; c1 = (k >> 1) * 192; }
            else { const int c = static_id(i); desc = T_K | (c << 8); c0 = 0; c1 = c * 128; bytes = SLOT_BYTES; }
        };
        if (lane == 0) {
#pragma unroll
            for (int i = NINIT; i < RING; i++) mbar_init(bar_full + i * 8, 1);
#pragma unroll
            for (int i = 0; i < RING; i++) mbar_init(bar_empty + i * 8, 4);
            asm volatile("fence.mbarrier_init.release.cluster;" ::: "memory");
        }
        uint32_t ent = 0;
        if (lane < n_stat) ent = (1u << 16) | (uint32_t)static_id(n_start + lane);
        sts_v32(sb + SM_LIST + lane * 4, ent);
        if (lane < 8) sts_v32(sb + SM_MISC + lane * 4, 0);
        __syncwarp();
        asm volatile("bar.arrive 2, 256;" ::: "memory");
        if (lane == 0) {
            int n = NINIT, landed = 0, slot = NINIT % RING, lslot = 0;
            uint32_t eph = NINIT == RING ? 0 : 1, lph = 0;
            int n_tail = 0;
            uint32_t unit = T_END;
            const int n_static = n_start + n_stat;
            int si = NINIT, kj = n_stat, vj = 0, ti = 0, asked = n_stat, vfree = 0;
            uint32_t t_last = clk(), ns_next = 0;
            bool exhausted = false;
            uint32_t pace = pace_ns, delay = ISSUE_DELAY;
            {
                uint32_t t1 = now_ns(), t2 = t1;
                while (t1 == t2 && clk() - t_last < 512) t1 = now_ns();
                t2 = t1;
                while (t1 == t2 && clk() - t_last < 1024) t2 = now_ns();
                if (t2 - t1 - 1u >= 64u || pace == 0) { pace = 0; delay = 2 * ISSUE_DELAY; }
            }
#pragma unroll 1
            while (true) {
                int cur = -1;
                if (!exhausted && si >= n_static - 2) {
                    if (asked == kj) {
                        if (asked - vfree < NBUF) sts_v32(sb + SM_MISC + 20, ++asked);
                    } else {
                        const uint32_t ent = lds_v32(sb + SM_LIST + (kj & (LISTN - 1)) * 4);
                        if ((ent >> 16) == (uint32_t)(kj / LISTN + 1)) {
                            cur = ent & 0xffffu;
                            if (cur == 0xffff && si >= n_static) {
                                exhausted = true;
                                unit = lds_v32(sb + SM_MISC + 16);
                                n_tail = (unit & 15) == T_WD ? 3 : ((unit & 15) == T_WO ? 2 : 0);
                            }
                        }
                    }
                }
                uint32_t desc, bytes = SLOT_BYTES;
                int c0 = 0, c1, lim = LIM;
                if (si < n_static) {
                    static_tile(si, desc, c0, c1, bytes);
                    lim = si < 6 ? LIM_START : LIM;
                    si++;
                } else if (vj < kj && (exhausted || (kj - vj > LAG && (int)lds_v32(sb + SM_MISC) > vj))) {
                    const uint32_t c = lds_v32(sb + SM_LIST + (vj & (LISTN - 1)) * 4) & 0xffffu;
                    desc = T_V | (c << 8);
                    c1 = (int)c * 128;
                    vj++;
                } else if (exhausted) {
                    sts_v32(sb + SM_MISC + 8, kj + 1);
                    if (ti == n_tail) break;
                    desc = unit | (ti << 4);
                    c0 = ((unit >> 8) & 15) * 64;
                    c1 = ((unit >> 12) * n_tail + ti) * 256;
                    ti++;
                } else if (cur >= 0) {
                    desc = T_K | (cur << 8);
                    c1 = cur * 128;
                    kj++;
                } else {
                    spin_guard(t_last);
                    continue;
                }
                mbar_wait(bar_empty + slot * 8, eph);
                if (n >= RING) vfree += (lds_v32(sb + SM_DESC + slot * 4) & 15) == T_V;
                sts_v32(sb + SM_DESC + slot * 4, desc);
                mbar_expect_tx(bar_full + slot * 8, bytes);
                while (n - landed >= lim) {
                    mbar_wait(bar_full + lslot * 8, lph);
                    landed++;
                    if (++lslot == RING) { lslot = 0; lph ^= 1; }
                }
                const uint32_t dly = n < 7 ? 0u : delay;
                for (const uint32_t t0 = clk(); clk() - t0 < dly;) {}
                uint32_t now = now_ns();
                if (n >= 7) {
                    while ((int)(now - ns_next) < 0 && clk() - t_last < 4096) now = now_ns();
                }
                ns_next = ((int)(now - ns_next) > PACE_CREDIT || n < 7 ? now - PACE_CREDIT : ns_next) + pace;
                tma3d(sb + SM_RING + slot * SLOT_BYTES, &maps.m[desc & 15], c0, c1, 0, bar_full + slot * 8, pol);
                t_last = clk();
                n++;
                if (++slot == RING) { slot = 0; eph ^= 1; }
            }
            if (n_tail == 0) {
                mbar_wait(bar_empty + slot * 8, eph);
                sts_v32(sb + SM_DESC + slot * 4, T_END);
                mbar_arrive(bar_full + slot * 8);
            }
        }
        return;
    }

    if (warp >= 4) {
        const int w = warp - 4, ct = tid - 128;
        const int g = lane >> 2, t = lane & 3, r8 = lane & 7, mi = lane >> 3;
        const uint32_t offK = (uint32_t)((32 * w + r8 + (mi & 1) * 8) * 128);
        const uint32_t xorK = (uint32_t)(((mi >> 1) ^ r8) << 4);
        const uint32_t rowT = (uint32_t)((r8 + (mi >> 1) * 8) * 128);
        const uint32_t offV0 = (uint32_t)((w >> 1) * 16384) + rowT + (uint32_t)((((4 * w & 7) + (mi & 1)) ^ r8) << 4);
        const uint32_t offV1 = (uint32_t)((w >> 1) * 16384) + rowT + (uint32_t)((((4 * w & 7) + 2 + (mi & 1)) ^ r8) << 4);
        const uint32_t offW = rowT + (uint32_t)(((2 * w + (mi & 1)) ^ r8) << 4);
        const uint32_t offB2 = (uint32_t)((lane & 1) * QROW + mi * 16);
        {
            const int row = 2 * w + (lane >> 4), hl = lane & 15;
            const uint2* xr = reinterpret_cast<const uint2*>(x + row * DM) + hl;
            uint2 xv[9];
            float sum = 0.f;
#pragma unroll
            for (int i = 0; i < 9; i++) xv[i] = __ldg(xr + 16 * i);
#pragma unroll
            for (int i = 0; i < 9; i++) sum += (bf_lo(xv[i].x) + bf_hi(xv[i].x)) + (bf_lo(xv[i].y) + bf_hi(xv[i].y));
#pragma unroll
            for (int o = 8; o; o >>= 1) sum += __shfl_xor_sync(~0u, sum, o);
            const float mean = sum * (1.f / DM);
            float var = 0.f;
#pragma unroll
            for (int i = 0; i < 9; i++) {
                const float a = bf_lo(xv[i].x) - mean, b = bf_hi(xv[i].x) - mean, c = bf_lo(xv[i].y) - mean, e = bf_hi(xv[i].y) - mean;
                var += (a * a + b * b) + (c * c + e * e);
            }
#pragma unroll
            for (int o = 8; o; o >>= 1) var += __shfl_xor_sync(~0u, var, o);
            const float mb = bfr(mean);
            const float rden = __frcp_rn(bfr(__fsqrt_rn(bfr(bfr(var * (1.f / DM)) + 1e-5f))));
#pragma unroll
            for (int i = 0; i < 9; i++) {
                const uint32_t d0 = pack_bf16(bf_lo(xv[i].x) - mb, bf_hi(xv[i].x) - mb);
                const uint32_t d1 = pack_bf16(bf_lo(xv[i].y) - mb, bf_hi(xv[i].y) - mb);
                const uint32_t v0 = pack_bf16(bf_lo(d0) * rden, bf_hi(d0) * rden), v1 = pack_bf16(bf_lo(d1) * rden, bf_hi(d1) * rden);
                sts_v64(sb + SM_XN + row * (XN_STRIDE * 2) + (hl + 16 * i) * 8, ((u64)v1 << 32) | v0);
            }
        }
        asm volatile("bar.sync 2, 256;" ::: "memory");
        const unsigned epoch = take_epoch();
        const uint32_t tag = epoch + 1u;
        float accA[2][4], accB[2][4];
        int slot = 0, kj = 0, vj = 0;
        uint32_t ph = 0;
        while (true) {
            mbar_wait(bar_full + slot * 8, ph);
            const uint32_t d = lds_v32(sb + SM_DESC + slot * 4);
            const int type = d & 15;
            const uint32_t tile = sb + SM_RING + slot * SLOT_BYTES;
            if (type == T_K) {
                const int e = kj & (NBUF - 1);
                mbar_wait(bar_qfull + e * 8, (kj / NBUF) & 1);
                uint32_t qf[4][4];
#pragma unroll
                for (int n = 0; n < 4; n++) ldsm4(qf[n], sb + SM_QBUF + e * (2 * QROW) + offB2 + n * 64);
                float c0[4] = {0.f, 0.f, 0.f, 0.f}, c1[4] = {0.f, 0.f, 0.f, 0.f};
                uint32_t a0[8][4], a1[8][4];
#pragma unroll
                for (int ks = 0; ks < 8; ks++) {
                    const uint32_t ad = tile + offK + (ks >> 2) * 16384 + (xorK ^ (uint32_t)((ks & 3) << 5));
                    ldsm4(a0[ks], ad);
                    ldsm4(a1[ks], ad + 2048);
                }
#pragma unroll
                for (int ks = 0; ks < 8; ks++) {
                    mma16816(c0, a0[ks], qf[ks >> 1][(ks & 1) * 2], qf[ks >> 1][(ks & 1) * 2 + 1]);
                    mma16816(c1, a1[ks], qf[ks >> 1][(ks & 1) * 2], qf[ks >> 1][(ks & 1) * 2 + 1]);
                }
                __syncwarp();
                if (lane == 0) mbar_arrive(bar_empty + slot * 8);
                const float SC = 0.08838834764831845f;
                uint32_t s[4];
                s[0] = pack_bf16(c0[0], c0[1]); s[1] = pack_bf16(c0[2], c0[3]);
                s[2] = pack_bf16(c1[0], c1[1]); s[3] = pack_bf16(c1[2], c1[3]);
#pragma unroll
                for (int i = 0; i < 4; i++) s[i] = pack_bf16(bf_lo(s[i]) * SC, bf_hi(s[i]) * SC);
                const uint32_t mine = t == 0 ? s[0] : t == 1 ? s[1] : t == 2 ? s[2] : s[3];
                sts_v32(sb + SM_SBUF + e * 512 + (32 * w + 8 * t + g) * 4, mine);
                uint32_t m2 = hmax2(hmax2(s[0], s[1]), hmax2(s[2], s[3]));
                m2 = hmax2(m2, __shfl_xor_sync(~0u, m2, 4));
                m2 = hmax2(m2, __shfl_xor_sync(~0u, m2, 8));
                m2 = hmax2(m2, __shfl_xor_sync(~0u, m2, 16));
                const uint32_t wm = sb + SM_WMAX + (kj & 1) * 16;
                if (lane == 0) sts_v32(wm + w * 4, m2);
                cons_sync();
                if (ct == 0) {
                    m2 = hmax2(hmax2(m2, lds_v32(wm + 4)), hmax2(lds_v32(wm + 8), lds_v32(wm + 12)));
                    st_relaxed(&g_s.mslot[d >> 8], ((u64)tag << 32) | m2);
                    mbar_arrive(bar_sfull + e * 8);
                }
                kj++;
            } else if (type == T_V) {
                const int e = vj & (NBUF - 1);
                uint32_t a0[8][4], a1[8][4];
#pragma unroll
                for (int ks = 0; ks < 8; ks++) {
                    ldsm4t(a0[ks], tile + offV0 + ks * 2048);
                    ldsm4t(a1[ks], tile + offV1 + ks * 2048);
                }
                mbar_wait(bar_pfull + e * 8, (vj / NBUF) & 1);
                uint32_t pf[4][4];
#pragma unroll
                for (int n = 0; n < 4; n++) ldsm4(pf[n], sb + SM_QBUF + e * (2 * QROW) + offB2 + n * 64);
                const float lsum = __uint_as_float(lds_v32(sb + SM_QBUF + e * (2 * QROW) + (g & 1) * QROW + 256));
                float c[4][4];
#pragma unroll
                for (int i = 0; i < 4; i++) c[i][0] = c[i][1] = c[i][2] = c[i][3] = 0.f;
#pragma unroll
                for (int ks = 0; ks < 8; ks++) {
                    mma16816(c[ks & 1], a0[ks], pf[ks >> 1][(ks & 1) * 2], pf[ks >> 1][(ks & 1) * 2 + 1]);
                    mma16816(c[2 + (ks & 1)], a1[ks], pf[ks >> 1][(ks & 1) * 2], pf[ks >> 1][(ks & 1) * 2 + 1]);
                }
                if (t < 3) {
                    const float v0 = t == 0 ? c[0][0] + c[1][0] : t == 1 ? c[0][1] + c[1][1] : c[2][2] + c[3][2];
                    const float v1 = t == 0 ? c[0][2] + c[1][2] : t == 1 ? c[0][3] + c[1][3] : c[2][3] + c[3][3];
                    const float v2 = t == 0 ? c[2][0] + c[3][0] : t == 1 ? c[2][1] + c[3][1] : lsum;
                    red_v4(g_s.oacc[d >> 14] + (t * 32 + w * 8 + g) * 4, v0, v1, v2, 1.0f);
                }
                __syncwarp();
                if (lane == 0) mbar_arrive(bar_empty + slot * 8);
                vj++;
                if (ct == 0) { sts_v32(sb + SM_MISC + 4, vj); sts_v32(sb + SM_MISC + 12, d >> 8); }
            } else if (type <= T_WU) {
                const int idx = (d >> 4) & 15;
                const uint32_t bad = sb + SM_XN + r8 * (XN_STRIDE * 2) + (idx * 192 + mi * 8) * 2;
                if (type == T_WU) {
                    if (idx == 0) {
#pragma unroll
                        for (int i = 0; i < 4; i++) accB[0][i] = accB[1][i] = 0.f;
                    }
                    wtile_mma<12>(accB, tile + offW, bad);
                } else {
                    if (idx == 0) {
#pragma unroll
                        for (int i = 0; i < 4; i++) accA[0][i] = accA[1][i] = 0.f;
                    }
                    wtile_mma<12>(accA, tile + offW, bad);
                }
                __syncwarp();
                if (lane == 0) mbar_arrive(bar_empty + slot * 8);
                if (idx == 2 && type != T_WG) {
#pragma unroll
                    for (int i = 0; i < 4; i++) {
                        float v = accA[0][i] + accA[1][i];
                        if (type == T_WU) {
                            const float gt = bfr(v), up = bfr(accB[0][i] + accB[1][i]);
                            const float inner = 0.7978845608028654f * (gt + 0.044715f * gt * gt * gt);
                            v = bfr(0.5f * gt * (1.f + tanhf(inner))) * up;
                        }
                        const int col = 16 * w + g + (i >> 1) * 8, b = 2 * t + (i & 1);
                        sts16(sb + SM_STAGE + (b * 64 + col) * 2, bf_bits(v));
                    }
                    cons_sync();
                    const int b = ct >> 4, c4 = ct & 15;
                    const u64 two = lds_v64(sb + SM_STAGE + (b * 64 + c4 * 4) * 2);
                    u64* dst = (type == T_WQ) ? &g_s.qtag[b * (HD / 2) + cta * 32 + c4 * 2]
                                              : &g_s.htag[b * (FF / 2) + gu_unit * 32 + c4 * 2];
                    st_relaxed_v2(dst, ((u64)tag << 32) | (two & 0xffffffffull), ((u64)tag << 32) | (two >> 32));
                    cons_sync();
                }
            } else if (type != T_END) {
                const int tail_cg = (d >> 8) & 15;
                const int ocol = tail_cg * 64 + 16 * w + g;
                uint32_t xq[4];
#pragma unroll
                for (int i = 0; i < 4; i++)
                    xq[i] = __ldg(reinterpret_cast<const unsigned short*>(x) + (2 * t + (i & 1)) * DM + ocol + (i >> 1) * 8);
                float r[4] = {0.f, 0.f, 0.f, 0.f};
                if (type == T_WD) {
                    mbar_wait(bar_act, 0);
                    float acc[4][4];
#pragma unroll
                    for (int i = 0; i < 4; i++) acc[i][0] = acc[i][1] = acc[i][2] = acc[i][3] = 0.f;
                    int sl = slot;
                    uint32_t pp = ph;
#pragma unroll 1
                    for (int ti = 0; ti < 3; ti++) {
                        uint32_t b[8][4], a[16][4];
#pragma unroll
                        for (int kk = 0; kk < 8; kk++) ldsm4(b[kk], sb + SM_ACT + r8 * (ACT_STRIDE * 2) + ti * 512 + mi * 16 + kk * 64);
                        mbar_spin(bar_full + sl * 8, pp);
#pragma unroll
                        for (int ks = 0; ks < 16; ks++) ldsm4t(a[ks], sb + SM_RING + sl * SLOT_BYTES + offW + ks * 2048);
#pragma unroll
                        for (int ks = 0; ks < 16; ks++) mma16816(acc[ks & 3], a[ks], b[ks >> 1][(ks & 1) * 2], b[ks >> 1][(ks & 1) * 2 + 1]);
                        if (++sl == RING) { sl = 0; pp ^= 1; }
                    }
#pragma unroll
                    for (int i = 0; i < 4; i++) r[i] = (acc[0][i] + acc[1][i]) + (acc[2][i] + acc[3][i]);
                } else {
                    int slot2 = slot + 1;
                    uint32_t ph2 = ph;
                    if (slot2 == RING) { slot2 = 0; ph2 ^= 1; }
                    const uint32_t tile2 = sb + SM_RING + slot2 * SLOT_BYTES;
                    const uint32_t bad = sb + SM_ACT + r8 * (ACT_STRIDE * 2) + mi * 16;
                    uint32_t a[2][16][4], b[8][4];
                    float acc[4][2][4];
#pragma unroll
                    for (int h = 0; h < 4; h++) {
#pragma unroll
                        for (int i = 0; i < 4; i++) acc[h][0][i] = acc[h][1][i] = 0.f;
                    }
                    auto load_b = [&](int hh) {
#pragma unroll
                        for (int i = 0; i < 8; i++) ldsm4(b[i], bad + (hh * 8 + i) * 64);
                    };
                    auto mma_half = [&](int hh) {
#pragma unroll
                        for (int kk = 0; kk < 4; kk++) {
#pragma unroll
                            for (int h2 = 0; h2 < 2; h2++) {
                                mma16816(acc[hh * 2 + h2][0], a[hh][h2 * 8 + 2 * kk], b[h2 * 4 + kk][0], b[h2 * 4 + kk][1]);
                                mma16816(acc[hh * 2 + h2][1], a[hh][h2 * 8 + 2 * kk + 1], b[h2 * 4 + kk][2], b[h2 * 4 + kk][3]);
                            }
                        }
                    };
#pragma unroll
                    for (int ks = 0; ks < 16; ks++) ldsm4t(a[0][ks], tile + offW + ks * 2048);
                    bool act_first;
                    for (const uint32_t t0 = clk();; spin_guard(t0)) {
                        act_first = __all_sync(~0u, mbar_test(bar_act, 0));
                        if (act_first || __all_sync(~0u, mbar_test(bar_full + slot2 * 8, ph2))) break;
                    }
                    if (act_first) {
                        load_b(0);
                        mma_half(0);
                        load_b(1);
                        mbar_spin(bar_full + slot2 * 8, ph2);
                    }
#pragma unroll
                    for (int ks = 0; ks < 16; ks++) ldsm4t(a[1][ks], tile2 + offW + ks * 2048);
                    if (!act_first) {
                        mbar_spin(bar_act, 0);
                        load_b(0);
                        mma_half(0);
                        load_b(1);
                    }
                    float4 li0, li1;
                    asm volatile("ld.shared.v4.f32 {%0,%1,%2,%3}, [%4];" : "=f"(li0.x), "=f"(li0.y), "=f"(li0.z), "=f"(li0.w)
                                 : "r"(sb + SM_LINV + t * 32) : "memory");
                    asm volatile("ld.shared.v4.f32 {%0,%1,%2,%3}, [%4];" : "=f"(li1.x), "=f"(li1.y), "=f"(li1.z), "=f"(li1.w)
                                 : "r"(sb + SM_LINV + t * 32 + 16) : "memory");
                    mma_half(1);
                    const float l0[4] = {li0.x, li0.y, li0.z, li0.w}, l1[4] = {li1.x, li1.y, li1.z, li1.w};
#pragma unroll
                    for (int h = 0; h < 4; h++) {
                        r[0] += (acc[h][0][0] + acc[h][1][0]) * l0[h];
                        r[1] += (acc[h][0][1] + acc[h][1][1]) * l1[h];
                        r[2] += (acc[h][0][2] + acc[h][1][2]) * l0[h];
                        r[3] += (acc[h][0][3] + acc[h][1][3]) * l1[h];
                    }
                }
                float4 o[4];
#pragma unroll
                for (int i = 0; i < 4; i++)
                    atom_v4(o[i], &g_s.facc[tail_cg * 4 + w][i][lane], type == T_WO ? r[i] : 0.f,
                               type == T_WO ? 0.f : r[i], 1.f);
#pragma unroll
                for (int i = 0; i < 4; i++) {
                    const float s = bfr(type == T_WO ? o[i].x + r[i] : o[i].x), f = bfr(type == T_WO ? o[i].y : o[i].y + r[i]);
                    const float gate = bfr(__fdividef(f, 1.f + __expf(-f)));
                    const uint32_t res = bf_bits(__uint_as_float(xq[i] << 16) + bfr(s * gate));
                    if (o[i].z == 13.f) reinterpret_cast<unsigned short*>(out)[(2 * t + (i & 1)) * DM + ocol + (i >> 1) * 8] = (unsigned short)res;
                }
                if (tail_cg == 0 && ct == 0 && o[0].z == 13.f)
                    asm volatile("st.relaxed.gpu.global.u32 [%0], %1;" ::"l"(&g_s.epoch), "r"(epoch + 1u) : "memory");
                break;
            } else {
                break;
            }
            if (++slot == RING) { slot = 0; ph ^= 1; }
        }
    } else {
        if (lane == 0) {
#pragma unroll 4
            for (int i = 0; i < NBUF; i++) mbar_init(bar_qfull + ((warp - 1) * NBUF + i) * 8, 1);
            if (warp == 3) mbar_init(bar_act, 2);
            else asm volatile("prefetch.tensormap [%0];" ::"l"(&maps.m[T_K + warp - 1]) : "memory");
            asm volatile("fence.mbarrier_init.release.cluster;" ::: "memory");
        }
        __syncwarp();
        asm volatile("bar.sync 2, 256;" ::: "memory");
        const unsigned epoch = take_epoch();
        const uint32_t tag = epoch + 1u;
        auto wait_cleared = [&]() {
            const uint32_t t0 = clk();
            while (true) {
                uint32_t f[4];
                asm volatile("ld.acquire.gpu.global.v4.u32 {%0,%1,%2,%3}, [%4];"
                             : "=r"(f[0]), "=r"(f[1]), "=r"(f[2]), "=r"(f[3]) : "l"(&g_s.zflag[lane * 4]) : "memory");
                if (__all_sync(~0u, f[0] == tag && f[1] == tag && f[2] == tag && f[3] == tag)) break;
                __nanosleep(500);
                spin_guard(t0);
            }
        };
        if (warp == 1) {
#pragma unroll 1
            for (int j = 0;; j++) {
                uint32_t ent, it = clk();
                while (((ent = lds_v32(sb + SM_LIST + (j & (LISTN - 1)) * 4)) >> 16) != (uint32_t)(j / LISTN + 1)) {
                    __nanosleep(100);
                    spin_guard(it);
                }
                const uint32_t c = ent & 0xffffu;
                if (c == 0xffffu) break;
                const u64* src = &g_s.qtag[(c >> 6) * 128 + lane * 4];
                u64 a0 = 0, a1 = 0, a2 = 0, a3 = 0;
                it = clk();
                while (true) {
                    ld_relaxed_v2(a0, a1, src);
                    ld_relaxed_v2(a2, a3, src + 2);
                    const bool ok = (uint32_t)(a0 >> 32) == tag && (uint32_t)(a1 >> 32) == tag &&
                                    (uint32_t)(a2 >> 32) == tag && (uint32_t)(a3 >> 32) == tag;
                    if (__all_sync(~0u, ok)) break;
                    __nanosleep(200);
                    spin_guard(it);
                }
                const int e = j & (NBUF - 1);
                const uint32_t dst = sb + SM_QBUF + e * (2 * QROW) + (lane >> 4) * QROW + (lane & 15) * 16;
                asm volatile("st.shared.v4.u32 [%0], {%1,%2,%3,%4};" ::"r"(dst), "r"((uint32_t)a0), "r"((uint32_t)a1),
                             "r"((uint32_t)a2), "r"((uint32_t)a3) : "memory");
                __syncwarp();
                if (lane == 0) mbar_arrive(bar_qfull + e * 8);
            }
        } else if (warp == 2) {
            __nanosleep(6000);
            wait_cleared();
#pragma unroll 1
            for (int j = 0;; j++) {
                uint32_t it = clk();
                const int jd = j + MDELAY + 1;
                while ((lds_v32(sb + SM_LIST + (jd & (LISTN - 1)) * 4) >> 16) != (uint32_t)(jd / LISTN + 1)) {
                    __nanosleep(100);
                    spin_guard(it);
                }
                const uint32_t c = lds_v32(sb + SM_LIST + (j & (LISTN - 1)) * 4) & 0xffffu;
                if (c == 0xffffu) break;
                const u64* src = &g_s.mslot[(c & ~63u) + lane * 2];
                u64 a0 = 0, a1 = 0;
                it = clk();
                while (true) {
                    ld_relaxed_v2(a0, a1, src);
                    const bool ok = (uint32_t)(a0 >> 32) == tag && (uint32_t)(a1 >> 32) == tag;
                    if (__all_sync(~0u, ok)) break;
                    __nanosleep(100);
                    spin_guard(it);
                }
                uint32_t m2 = hmax2((uint32_t)a0, (uint32_t)a1);
#pragma unroll
                for (int o = 16; o; o >>= 1) m2 = hmax2(m2, __shfl_xor_sync(~0u, m2, o));
                const int e = j & (NBUF - 1);
                mbar_wait(bar_sfull + e * 8, (j / NBUF) & 1);
                uint32_t s4[4];
                asm volatile("ld.shared.v4.u32 {%0,%1,%2,%3}, [%4];" : "=r"(s4[0]), "=r"(s4[1]), "=r"(s4[2]), "=r"(s4[3])
                             : "r"(sb + SM_SBUF + e * 512 + lane * 16) : "memory");
                const float L2E = 1.4426950408889634f, m0 = bf_lo(m2), m1 = bf_hi(m2);
                float p0[4], p1[4];
#pragma unroll
                for (int i = 0; i < 4; i++) { p0[i] = exp2f((bf_lo(s4[i]) - m0) * L2E); p1[i] = exp2f((bf_hi(s4[i]) - m1) * L2E); }
                const uint32_t pb = sb + SM_QBUF + e * (2 * QROW) + lane * 8;
                const uint32_t q0 = pack_bf16(p0[0], p0[1]), q1 = pack_bf16(p0[2], p0[3]);
                const uint32_t q2 = pack_bf16(p1[0], p1[1]), q3 = pack_bf16(p1[2], p1[3]);
                sts_v64(pb, ((u64)q1 << 32) | q0);
                sts_v64(pb + QROW, ((u64)q3 << 32) | q2);
                float l0 = (bf_lo(q0) + bf_hi(q0)) + (bf_lo(q1) + bf_hi(q1)), l1 = (bf_lo(q2) + bf_hi(q2)) + (bf_lo(q3) + bf_hi(q3));
#pragma unroll
                for (int o = 16; o; o >>= 1) { l0 += __shfl_xor_sync(~0u, l0, o); l1 += __shfl_xor_sync(~0u, l1, o); }
                if (lane < 2) sts_v32(sb + SM_QBUF + e * (2 * QROW) + lane * QROW + 256, __float_as_uint(lane ? l1 : l0));
                __syncwarp();
                if (lane == 0) {
                    mbar_arrive(bar_pfull + e * 8);
                    sts_v32(sb + SM_MISC, j + 1);
                }
            }
        } else {
            if (cta < 128) {
                float4* z = reinterpret_cast<float4*>(g_s.oacc[cta]);
#pragma unroll
                for (int i = 0; i < OACC_STRIDE / 128; i++) z[lane + 32 * i] = make_float4(0.f, 0.f, 0.f, 0.f);
                if (cta < 72) {
                    float4* zf = &g_s.facc[0][0][0] + cta * 64;
                    zf[lane] = zf[lane + 32] = make_float4(0.f, 0.f, 0.f, 0.f);
                }
                __threadfence();
                __syncwarp();
                if (lane == 0) asm volatile("st.relaxed.gpu.global.u32 [%0], %1;" ::"l"(&g_s.zflag[cta]), "r"(tag) : "memory");
            } else if (cta == 128 && lane == 0) {
                g_s.ctr[(epoch & 1) ^ 1][0] = 0;
            }
            if (lane < 2) asm volatile("prefetch.tensormap [%0];" ::"l"(&maps.m[T_WO + lane]) : "memory");
            if (lane == 0) {
#pragma unroll 1
                for (int j = cta >= 4 ? NSTATK : 0;; j++) {
                    const uint32_t t0 = clk();
                    while ((int)lds_v32(sb + SM_MISC + 20) <= j) {
                        __nanosleep(40);
                        spin_guard(t0);
                    }
                    const uint32_t c = atomicAdd(&g_s.ctr[epoch & 1][0], 1u) + NSTATK * 128;
                    if (c >= NCHUNK) {
                        const int rank = c - NCHUNK, u = rank < 54 ? rank : rank - 54;
                        sts_v32(sb + SM_MISC + 16, (rank < 54 ? T_WD : (rank < 126 ? T_WO : T_END)) | ((u % 9) << 8) | ((u / 9) << 12));
#pragma unroll 1
                        for (int i = j; i < j + MDELAY + 2; i++)
                            sts_v32(sb + SM_LIST + (i & (LISTN - 1)) * 4, (uint32_t)((i / LISTN + 1) << 16) | 0xffffu);
                        break;
                    }
                    sts_v32(sb + SM_LIST + (j & (LISTN - 1)) * 4, (uint32_t)((j / LISTN + 1) << 16) | c);
                }
            }
            __syncwarp();
        }
        if (warp != 2) {
            uint32_t unit;
            uint32_t it = clk();
            while ((unit = lds_v32(sb + SM_MISC + 16)) == 0) {
                __nanosleep(500);
                spin_guard(it);
            }
            const int tail_type = unit & 15, tail_rg = unit >> 12, b0 = warp == 1 ? 0 : 4;
            wait_cleared();
            if (tail_type == T_WD) {
#pragma unroll 1
                for (int b = b0; b < b0 + 4; b++) {
                    const u64* src = &g_s.htag[b * (FF / 2) + tail_rg * 384 + lane * 2];
                    u64 a[12];
                    it = clk();
                    while (true) {
                        bool ok = true;
#pragma unroll
                        for (int i = 0; i < 6; i++) ld_relaxed_v2(a[2 * i], a[2 * i + 1], src + i * 64);
#pragma unroll
                        for (int i = 0; i < 12; i++) ok = ok && (uint32_t)(a[i] >> 32) == tag;
                        if (__all_sync(~0u, ok)) break;
                        __nanosleep(500);
                        spin_guard(it);
                    }
#pragma unroll
                    for (int i = 0; i < 6; i++)
                        sts_v64(sb + SM_ACT + b * (ACT_STRIDE * 2) + (i * 64 + lane * 2) * 4,
                                (a[2 * i] & 0xffffffffull) | (a[2 * i + 1] << 32));
                }
            } else if (tail_type == T_WO) {
#pragma unroll 1
                for (int b = b0; b < b0 + 4; b++) {
                    const int pair0 = b * 16 + 2 * tail_rg;
                    it = clk();
                    while (lds_v32(sb + SM_MISC + 12) < (uint32_t)(pair0 + 2) * 64 && lds_v32(sb + SM_MISC + 8) - 1u > lds_v32(sb + SM_MISC + 4)) {
                        __nanosleep(100);
                        spin_guard(it);
                    }
                    const float4* src = reinterpret_cast<const float4*>(g_s.oacc[pair0]) + lane;
                    float4 v[6];
                    it = clk();
                    while (true) {
                        bool ok = true;
#pragma unroll
                        for (int i = 0; i < 6; i++) ld_relaxed_f4(v[i], src + i * 32);
#pragma unroll
                        for (int i = 0; i < 6; i++) ok = ok && v[i].w == 64.0f;
                        if (__all_sync(~0u, ok)) break;
                        spin_guard(it);
                    }
                    const uint32_t ab = sb + SM_ACT + b * (ACT_STRIDE * 2) + ((lane >> 3) * 32 + (lane & 7)) * 2;
#pragma unroll
                    for (int k = 0; k < 2; k++) {
                        sts16(ab + k * 512, bf_bits(v[3 * k].x));
                        sts16(ab + k * 512 + 16, bf_bits(v[3 * k].y));
                        sts16(ab + k * 512 + 32, bf_bits(v[3 * k].z));
                        sts16(ab + k * 512 + 48, bf_bits(v[3 * k + 2].x));
                        sts16(ab + k * 512 + 256, bf_bits(v[3 * k + 1].x));
                        sts16(ab + k * 512 + 256 + 16, bf_bits(v[3 * k + 1].y));
                        sts16(ab + k * 512 + 256 + 32, bf_bits(v[3 * k + 1].z));
                        sts16(ab + k * 512 + 256 + 48, bf_bits(v[3 * k + 2].y));
                        if (lane < 2) sts_v32(sb + SM_LINV + (b * 4 + k * 2 + lane) * 4, __float_as_uint(__fdividef(1.f, v[3 * k + 2].z)));
                    }
                }
            }
            __syncwarp();
            if (lane == 0) mbar_arrive(bar_act);
        }
    }
}

struct FallbackScratch { float xn[8 * DM], q[8 * HD], o[8 * HD], g[8 * FF], u[8 * FF], s[8 * DM], f[8 * DM]; };
__device__ FallbackScratch g_fb;

__device__ float block_reduce(float v, bool is_max, float* red) {
    for (int o = 16; o; o >>= 1) { const float y = __shfl_xor_sync(~0u, v, o); v = is_max ? fmaxf(v, y) : v + y; }
    __syncthreads();
    if ((threadIdx.x & 31) == 0) red[threadIdx.x >> 5] = v;
    __syncthreads();
    v = red[0];
    for (int i = 1; i < (int)blockDim.x / 32; i++) v = is_max ? fmaxf(v, red[i]) : v + red[i];
    return v;
}
__global__ void fb_ln(const __nv_bfloat16* x) {
    __shared__ float red[32];
    const float v = __bfloat162float(x[blockIdx.x * DM + threadIdx.x]);
    const float mean = block_reduce(v, false, red) / DM;
    const float var = block_reduce((v - mean) * (v - mean), false, red) / DM;
    g_fb.xn[blockIdx.x * DM + threadIdx.x] = bfr(bfr(v - bfr(mean)) / bfr(sqrtf(bfr(bfr(var) + 1e-5f))));
}
__global__ void fb_gemv(int which, const __nv_bfloat16* w, int K, int N) {
    const float* a = which == 3 ? g_fb.o : which == 4 ? g_fb.g : g_fb.xn;
    float* o = which == 0 ? g_fb.q : which == 1 ? g_fb.g : which == 2 ? g_fb.u : which == 3 ? g_fb.s : g_fb.f;
    const int n = blockIdx.x * 64 + threadIdx.x, b = blockIdx.y;
    float acc = 0.f;
    for (int k = 0; k < K; k++) acc += a[b * K + k] * __bfloat162float(w[(size_t)k * N + n]);
    o[b * N + n] = bfr(acc);
}
__global__ void fb_geglu() {
    const int i = blockIdx.x * 256 + threadIdx.x;
    const float gt = g_fb.g[i];
    g_fb.g[i] = bfr(bfr(0.5f * gt * (1.f + tanhf(0.7978845608028654f * (gt + 0.044715f * gt * gt * gt)))) * g_fb.u[i]);
}
__global__ void fb_attn(const __nv_bfloat16* K, const __nv_bfloat16* V) {
    __shared__ float sc[8192], qv[128], red[32], part[4][128];
    const int bh = blockIdx.x, tid = threadIdx.x;
    const size_t base = (size_t)((bh >> 5) * 16 + ((bh & 31) >> 1)) * 8192 * 128;
    if (tid < 128) qv[tid] = g_fb.q[bh * 128 + tid];
    __syncthreads();
    float m = -INFINITY;
    for (int s = tid; s < 8192; s += 512) {
        float a = 0.f;
        for (int d = 0; d < 128; d++) a += qv[d] * __bfloat162float(K[base + (size_t)s * 128 + d]);
        sc[s] = bfr(bfr(a) * 0.08838834764831845f);
        m = fmaxf(m, sc[s]);
    }
    m = block_reduce(m, true, red);
    float l = 0.f;
    for (int s = tid; s < 8192; s += 512) { sc[s] = expf(sc[s] - m); l += sc[s]; }
    l = block_reduce(l, false, red);
    float acc = 0.f;
    for (int s = tid >> 7; s < 8192; s += 4) acc += bfr(sc[s] / l) * __bfloat162float(V[base + (size_t)s * 128 + (tid & 127)]);
    part[tid >> 7][tid & 127] = acc;
    __syncthreads();
    if (tid < 128) g_fb.o[bh * 128 + tid] = bfr(part[0][tid] + part[1][tid] + part[2][tid] + part[3][tid]);
}
__global__ void fb_out(const __nv_bfloat16* x, __nv_bfloat16* out) {
    const int i = blockIdx.x * 256 + threadIdx.x;
    const float f = g_fb.f[i];
    out[i] = __float2bfloat16_rn(__bfloat162float(x[i]) + bfr(g_fb.s[i] * bfr(f / (1.f + expf(-f)))));
}

typedef CUresult (*EncodeFn)(CUtensorMap*, CUtensorMapDataType, cuuint32_t, void*, const cuuint64_t*, const cuuint64_t*,
                             const cuuint32_t*, const cuuint32_t*, CUtensorMapInterleave, CUtensorMapSwizzle,
                             CUtensorMapL2promotion, CUtensorMapFloatOOBfill);

void make_kv_map(EncodeFn enc, CUtensorMap* m, void* base) {
    cuuint64_t dims[3] = {64, (cuuint64_t)NCHUNK * 128, 2};
    cuuint64_t str[2] = {256, 128};
    cuuint32_t box[3] = {64, 128, 2};
    cuuint32_t es[3] = {1, 1, 1};
    enc(m, CU_TENSOR_MAP_DATA_TYPE_BFLOAT16, 3, base, dims, str, box, es, CU_TENSOR_MAP_INTERLEAVE_NONE,
        CU_TENSOR_MAP_SWIZZLE_128B, CU_TENSOR_MAP_L2_PROMOTION_L2_256B, CU_TENSOR_MAP_FLOAT_OOB_FILL_NONE);
}
void make_w_map(EncodeFn enc, CUtensorMap* m, void* base, int rows, int cols, int box_rows) {
    cuuint64_t dims[3] = {(cuuint64_t)cols, (cuuint64_t)rows, 1};
    cuuint64_t str[2] = {(cuuint64_t)cols * 2, (cuuint64_t)cols * 2 * rows};
    cuuint32_t box[3] = {64, (cuuint32_t)box_rows, 1};
    cuuint32_t es[3] = {1, 1, 1};
    enc(m, CU_TENSOR_MAP_DATA_TYPE_BFLOAT16, 3, base, dims, str, box, es, CU_TENSOR_MAP_INTERLEAVE_NONE,
        CU_TENSOR_MAP_SWIZZLE_128B, CU_TENSOR_MAP_L2_PROMOTION_L2_128B, CU_TENSOR_MAP_FLOAT_OOB_FILL_NONE);
}

}

extern "C" void kernel_launch(void* const* d_in, const int* in_sizes, int n_in, void* d_out, int out_size) {
    (void)in_sizes; (void)n_in; (void)out_size;
    typedef const __nv_bfloat16* bfp;
    static int mode = -1;
    static EncodeFn enc = nullptr;
    static uint32_t pace_ns = 0;
    if (mode < 0) {
        void* fn = nullptr;
        cudaDriverEntryPointQueryResult qr;
        cudaGetDriverEntryPoint("cuTensorMapEncodeTiled", &fn, cudaEnableDefault, &qr);
        enc = (EncodeFn)fn;
        int dev = 0, sms = 0, per_sm = 0;
        cudaGetDevice(&dev);
        cudaDeviceGetAttribute(&sms, cudaDevAttrMultiProcessorCount, dev);
        int mem_khz = 0, bus_bits = 0;
        cudaDeviceGetAttribute(&mem_khz, cudaDevAttrMemoryClockRate, dev);
        cudaDeviceGetAttribute(&bus_bits, cudaDevAttrGlobalMemoryBusWidth, dev);
        const double peak_bytes_per_ns = 2.0 * mem_khz * 1e3 * (bus_bits / 8) * 1e-9;
        if (peak_bytes_per_ns > 1000.0) pace_ns = (uint32_t)(PACE * GRID * SLOT_BYTES / peak_bytes_per_ns);
        const bool ok = enc != nullptr &&
            cudaFuncSetAttribute(fused_decode_kernel, cudaFuncAttributeMaxDynamicSharedMemorySize, SMEM_BYTES) == cudaSuccess &&
            cudaOccupancyMaxActiveBlocksPerMultiprocessor(&per_sm, fused_decode_kernel, NTHR, SMEM_BYTES) == cudaSuccess &&
            sms * per_sm >= GRID;
        (void)cudaGetLastError();
        mode = ok ? 1 : 0;
    }
    cudaStream_t st = cudaStreamPerThread;
    if (mode == 0) {
        fb_ln<<<8, DM, 0, st>>>((bfp)d_in[0]);
        fb_gemv<<<dim3(HD / 64, 8), 64, 0, st>>>(0, (bfp)d_in[3], DM, HD);
        fb_gemv<<<dim3(FF / 64, 8), 64, 0, st>>>(1, (bfp)d_in[6], DM, FF);
        fb_gemv<<<dim3(FF / 64, 8), 64, 0, st>>>(2, (bfp)d_in[7], DM, FF);
        fb_geglu<<<8 * FF / 256, 256, 0, st>>>();
        fb_attn<<<256, 512, 0, st>>>((bfp)d_in[1], (bfp)d_in[2]);
        fb_gemv<<<dim3(DM / 64, 8), 64, 0, st>>>(3, (bfp)d_in[4], HD, DM);
        fb_gemv<<<dim3(DM / 64, 8), 64, 0, st>>>(4, (bfp)d_in[8], FF, DM);
        fb_out<<<8 * DM / 256, 256, 0, st>>>((bfp)d_in[0], (__nv_bfloat16*)d_out);
        return;
    }
    Maps maps;
    make_kv_map(enc, &maps.m[T_K], d_in[1]);
    make_kv_map(enc, &maps.m[T_V], d_in[2]);
    make_w_map(enc, &maps.m[T_WQ], d_in[3], DM, HD, 192);
    make_w_map(enc, &maps.m[T_WO], d_in[4], HD, DM, 256);
    make_w_map(enc, &maps.m[T_WG], d_in[6], DM, FF, 192);
    make_w_map(enc, &maps.m[T_WU], d_in[7], DM, FF, 192);
    make_w_map(enc, &maps.m[T_WD], d_in[8], FF, DM, 256);
    fused_decode_kernel<<<GRID, NTHR, SMEM_BYTES, st>>>((const char*)d_in[3], (const char*)d_in[6], (const char*)d_in[7],
                                                        (bfp)d_in[0], (__nv_bfloat16*)d_out, pace_ns, maps);
}
```
